```python
import torch

def _softmax(x, axis=-1):
    return torch.softmax(x, dim=axis)
def _gelu(x):
    return torch.nn.functional.gelu(x, approximate="tanh")
def _silu(x):
    return torch.nn.functional.silu(x)
def _sigmoid(x):
    return torch.sigmoid(x)
def _layernorm(x, axis=-1, eps=1e-5):
    m = x.mean(dim=axis, keepdim=True)
    v = x.var(dim=axis, keepdim=True, unbiased=False)
    return (x - m) / torch.sqrt(v + eps)
def _scatter_add(tgt, idx, src, axis=0):
    return tgt.clone().index_add_(axis, idx, src)
def _segment_sum(src, seg, n):
    out = torch.zeros((n,) + src.shape[1:], dtype=src.dtype)
    return out.index_add_(0, seg, src)
def _pad(x, pw):
    flat = tuple(v for pair in reversed(pw) for v in pair)
    return torch.nn.functional.pad(x, flat)

kernel_name = 'recurrent_scan__linear_kernel_hedgehog__dense_activation_silu__prompt'

def setup_inputs():

    _w = (lambda a: (lambda t: t.to(torch.bfloat16) if t.is_floating_point() else t)(torch.as_tensor(a)))
    def _A_setup():
        B, S, D, H = 1, 2048, 640, 32
        Dh = D // H
        return {
            "x": _w((lambda *s: torch.randn(*s, dtype=torch.bfloat16) * 0.05)(B, S, D)),
            "wqkv": _w((lambda *s: torch.randn(*s, dtype=torch.bfloat16) * 0.4)(D, 3 * D)),
            "w_phi": _w((lambda *s: torch.randn(*s, dtype=torch.bfloat16) * 0.4)(H, Dh, Dh) * (Dh ** -0.5)),
            "wo": _w((lambda *s: torch.randn(*s, dtype=torch.bfloat16) * 0.2)(D, D)),
        }
    _A_in = _A_setup()

    def _B_setup():
        B, S, D, F = 1, 2048, 640, 1728
        return {
            "x": _w((lambda *s: torch.randn(*s, dtype=torch.bfloat16) * 0.05)(B, S, D)),
            "w1": _w((lambda *s: torch.randn(*s, dtype=torch.bfloat16) * 0.4)(D, F) * (D ** -0.5)),
            "w2": _w((lambda *s: torch.randn(*s, dtype=torch.bfloat16) * 0.1)(F, D) * (F ** -0.5)),
        }
    _B_in = _B_setup()

    return {
        "A_x": _A_in["x"],
        "A_wqkv": _A_in["wqkv"],
        "A_w_phi": _A_in["w_phi"],
        "A_wo": _A_in["wo"],
        "B_x": _B_in["x"],
        "B_w1": _B_in["w1"],
        "B_w2": _B_in["w2"],
    }

def reference(A_x, A_wqkv, A_w_phi, A_wo, B_x, B_w1, B_w2):
    def _A_ref(x, wqkv, w_phi, wo):
        B, S, D = x.shape
        H = 32; Dh = D // H
        qkv = (lambda x, *d: x.permute(*d))((x @ wqkv).reshape(B, S, 3, H, Dh), 2, 0, 3, 1, 4)
        q, k, v = qkv[0], qkv[1], qkv[2]
        pq = torch.einsum("bhsd,hdf->bhsf", q, w_phi)
        pk = torch.einsum("bhsd,hdf->bhsf", k, w_phi)
        phi_q = torch.concatenate([_softmax(pq, axis=-1), _softmax(-pq, axis=-1)], axis=-1)
        phi_k = torch.concatenate([_softmax(pk, axis=-1), _softmax(-pk, axis=-1)], axis=-1)
        kv = torch.einsum("bhsf,bhsd->bhfd", phi_k, v)
        z  = torch.einsum("bhsf->bhf", phi_k)
        num = torch.einsum("bhqf,bhfd->bhqd", phi_q, kv)
        den = torch.einsum("bhqf,bhf->bhq", phi_q, z)[..., None] + 1e-6
        o = num / den
        return (lambda x, *d: x.permute(*d))(o, 0, 2, 1, 3).reshape(B, S, D) @ wo

    def _B_ref(x, w1, w2):
        h = torch.einsum("bsd,df->bsf", x, w1)
        h = _silu(h)
        out = torch.einsum("bsf,fd->bsd", h, w2)
        return out

    x = A_x
    xn = _layernorm(x, axis=-1)
    s = _A_ref(xn, A_wqkv, A_w_phi, A_wo)
    g = _silu(_B_ref(xn, B_w1, B_w2))
    return x + s * g
```

```cpp
#include <cuda_runtime.h>
#include <cuda.h>
#include <cuda_bf16.h>
#include <stdint.h>

#define USE_MC 1
#define NPRE1 1
#define PFLEAD 2
#define XG_A 0x8530
#define XG_B 0x9742
#define W1A_LAG 1
#define JB 10
#define PFW_X 0
#define J1_DELAY 2500
#define J2_DELAY 0
#define JPOS 7
#define JA 3
#define JV 2
#define PFALL 0
#define E1_DIST 20
#define E1_TAP 1
#define NPRE2 1
#define KV_FIRST 1
#define LL_PRE 0
#define HB_X 7
#define EXTRA_FIRST 0
#define KSIG_K 8
#define KSIG_Q 5
#define HA_SPLIT 32
#define NPOISON 40
#define PF2_ST 1
#define KV_BUF0 1
#define KSPLIT (KV_BUF0 ? 8 : 6)
#define MAXOUT 0
#define QPAUSE 5
#define WAVE2_DELAY 600
#define J2_K0 2
#define XLEAD 2
#define MAP_MODE 2

namespace {

constexpr int kD = 640, kF = 1728;
constexpr float kLog2e = 1.4426950408889634f;

constexpr uint32_t RING_OFF = 163840, SLOT = 12288, WPHI_OFF = RING_OFF + 4 * SLOT, MISC_OFF = 229152, SMEM_BYTES = 232448;
constexpr uint32_t RING0 = RING_OFF - 3 * SLOT;
constexpr uint32_t BAR_X = MISC_OFF, BAR_PRO = BAR_X + 96, BAR_WPHI = BAR_PRO + 8, BAR_DUMMY = BAR_PRO + 16, BAR_GOK = BAR_PRO + 24, BAR_KV = BAR_WPHI  , BAR_XR = BAR_PRO  , BAR_RF = BAR_X + 128, BAR_RF1 = BAR_RF + 64,
                   BAR_RE = BAR_RF1 + 64, BAR_BE = BAR_RE + 64, BAR_BF = BAR_BE + 32, BAR_BF1 = BAR_BF + 32, BAR_CS = BAR_BF1 + 32;
constexpr uint32_t CS_OFF = 229600, ST_OFF = CS_OFF + 1824;
static_assert(BAR_CS + 32 <= CS_OFF && ST_OFF + 1024 <= SMEM_BYTES, "smem map");
constexpr int CS_W1A = 0, CS_K = 128, CS_W1B = 208, CS_Q = 296, CS_V = 376;
constexpr uint32_t BUF_BYTES = 40960;
constexpr uint32_t KVB_OFF = RING_OFF, PHI_HALF = 20608;
constexpr uint32_t V_OFF = KV_BUF0 * 40960, PHIK_OFF = V_OFF + 26624;
constexpr uint32_t G_OFF = RING_OFF, Y_OFF = RING_OFF + 20480, O_OFF = RING_OFF + 40960;
static_assert(O_OFF + 20480 <= MISC_OFF && Y_OFF % 128 == 0, "scratch");
constexpr uint32_t V_PITCH = 208, PHI_HS = 5152;
constexpr int NCTA_MC = USE_MC ? 2 : 1;

#define P1_ORDER "AVAVAVAAVAVAVAAVAVAVAVAA"
#define P1_SLOTS "012345670123456734567345"
#define P1_XPOS  "..x.x..x.x.x..x.x.x..x.."
constexpr uint32_t order_mask(const char* p, char ch) { uint32_t m = 0; for (int i = 0; p[i]; i++) if (p[i] == ch) m |= 1u << i; return m; }
constexpr uint64_t order_slots(char ch) { uint64_t m = 0; int n = 0; for (int i = 0; i < 24; i++) if (P1_ORDER[i] == ch) { m |= (uint64_t)(P1_SLOTS[i] - '0') << (4 * n); n++; } return m; }
constexpr uint32_t order_phase(char ch) { uint32_t m = 0; for (int i = 0; i < 24; i++) { int id = P1_SLOTS[i] - '0'; if ((ch == 0 || P1_ORDER[i] == ch) && id >= 3 && id < 7) m ^= 1u << (8 * (id - 3)); } return m; }
constexpr uint32_t P1_MASK = order_mask(P1_ORDER, 'A'), P1_XMASK = order_mask(P1_XPOS, 'x');
constexpr uint64_t P1_SLOT_A = order_slots('A'), P1_SLOT_V = order_slots('V');
constexpr uint32_t PH_A = order_phase('A'), PH_V = order_phase('V'), PH_ALL = order_phase(0);
constexpr int POS_K = 3, POS_W1B = 1;

struct Maps { CUtensorMap x, w1a, q32, q16, jq, jw, w1_32, w1_24, w2_64, w2_32, wo_64, wo_16, y, xr; };

__device__ uint4 g_h[16 * 216 * 128];
__device__ uint4 g_o[16 * 80 * 128];
__device__ uint4 g_part[128 * 10 * 128];
__device__ float4 g_kv[8 * 4 * 10 * 32];
__device__ uint4 g_stats[2048];
__device__ uint4 g_colsum[8 * 228];
__device__ uint4 g_wphi[8 * 800];
__device__ unsigned g_pro[32];
__device__ unsigned g_ha[32 * 32], g_hb[32 * 32], g_oc[128 * 32];
#define STAMP2_IF(c, id)
#define STAMP(id)
#define STAMP_IF(c, id)
#define ERRFLAG
__device__ __forceinline__ uint32_t smem_u32(const void* p) { return (uint32_t)__cvta_generic_to_shared(p); }
__device__ __forceinline__ void mbar_init(uint32_t bar, uint32_t cnt) { asm volatile("mbarrier.init.shared::cta.b64 [%0], %1;" ::"r"(bar), "r"(cnt)); }
__device__ __forceinline__ void mbar_expect_tx(uint32_t bar, uint32_t bytes) { asm volatile("mbarrier.arrive.expect_tx.shared::cta.b64 _, [%0], %1;" ::"r"(bar), "r"(bytes) : "memory"); }
__device__ __forceinline__ void mbar_arrive(uint32_t bar) { asm volatile("mbarrier.arrive.shared::cta.b64 _, [%0];" ::"r"(bar) : "memory"); }
__device__ __forceinline__ void mbar_arrive_n(uint32_t bar, uint32_t n) { asm volatile("mbarrier.arrive.shared::cta.b64 _, [%0], %1;" ::"r"(bar), "r"(n) : "memory"); }
__device__ __forceinline__ void mbar_arrive_cluster(uint32_t bar, uint32_t cta) {
  asm volatile("{\n.reg .b32 ra;\nmapa.shared::cluster.u32 ra, %0, %1;\nmbarrier.arrive.shared::cluster.b64 _, [ra];\n}" ::"r"(bar), "r"(cta) : "memory");
}
__device__ __forceinline__ void mbar_wait(uint32_t bar, uint32_t parity) {
  asm volatile("{\n.reg .pred p;\n.reg .u32 c;\nmov.u32 c, 0;\nWL:\nmbarrier.try_wait.parity.shared::cta.b64 p, [%0], %1;\n@p bra WD;\nadd.u32 c, c, 1;\nsetp.lt.u32 p, c, 262144;\n@p bra WL;\nWD:\n}" ::"r"(bar), "r"(parity) : "memory");
}
__device__ __forceinline__ bool elect_one() {
  uint32_t p;
  asm volatile("{\n.reg .pred P;\nelect.sync _|P, 0xffffffff;\nselp.u32 %0, 1, 0, P;\n}" : "=r"(p));
  return p;
}
__device__ __forceinline__ void tma2d(uint32_t dst, const CUtensorMap* m, int c0, int c1, uint32_t bar) {
  asm volatile("cp.async.bulk.tensor.2d.shared::cluster.global.mbarrier::complete_tx::bytes [%0], [%1, {%3, %4}], [%2];" ::"r"(dst), "l"(m), "r"(bar), "r"(c0), "r"(c1) : "memory");
}
__device__ __forceinline__ void tma2d_mc(uint32_t dst, const CUtensorMap* m, int c0, int c1, uint32_t bar) {
  asm volatile("cp.async.bulk.tensor.2d.shared::cluster.global.mbarrier::complete_tx::bytes.multicast::cluster [%0], [%1, {%3, %4}], [%2], %5;" ::"r"(dst), "l"(m), "r"(bar), "r"(c0), "r"(c1), "h"((uint16_t)3) : "memory");
}
__device__ __forceinline__ void tma3d(uint32_t dst, const CUtensorMap* m, int c0, int c1, uint32_t bar) {
  asm volatile("cp.async.bulk.tensor.3d.shared::cluster.global.mbarrier::complete_tx::bytes [%0], [%1, {%3, %4, %5}], [%2];" ::"r"(dst), "l"(m), "r"(bar), "r"(c0), "r"(c1), "r"(0) : "memory");
}
__device__ __forceinline__ void tma3d_mc(uint32_t dst, const CUtensorMap* m, int c0, int c1, uint32_t bar) {
  asm volatile("cp.async.bulk.tensor.3d.shared::cluster.global.mbarrier::complete_tx::bytes.multicast::cluster [%0], [%1, {%3, %4, %5}], [%2], %6;" ::"r"(dst), "l"(m), "r"(bar), "r"(c0), "r"(c1), "r"(0), "h"((uint16_t)3) : "memory");
}
__device__ __forceinline__ void prefetch_l2(const void* p) { asm volatile("prefetch.global.L2 [%0];" ::"l"(p)); }
__device__ __forceinline__ void tma_pair(uint32_t dst, const CUtensorMap* m, int c0, int row0, int half_rows, uint32_t bar, uint32_t rank) {
  tma2d_mc(dst + rank * half_rows * 128, m, c0, row0 + rank * half_rows, bar);
}
__device__ __forceinline__ void bulk_g2s(uint32_t dst, const void* src, uint32_t bytes, uint32_t bar) {
  asm volatile("cp.async.bulk.shared::cluster.global.mbarrier::complete_tx::bytes [%0], [%1], %2, [%3];" ::"r"(dst), "l"(src), "r"(bytes), "r"(bar) : "memory");
}
__device__ __forceinline__ void prefetch_map(const CUtensorMap* m) { asm volatile("prefetch.tensormap [%0];" ::"l"(m) : "memory"); }
__device__ __forceinline__ void wg_fence() { asm volatile("wgmma.fence.sync.aligned;" ::: "memory"); }
__device__ __forceinline__ void wg_commit() { asm volatile("wgmma.commit_group.sync.aligned;" ::: "memory"); }
template <int N> __device__ __forceinline__ void wg_wait() { asm volatile("wgmma.wait_group.sync.aligned %0;" ::"n"(N) : "memory"); }
template <int R> __device__ __forceinline__ void reg_fence(float (&d)[R]) {
#pragma unroll
  for (int i = 0; i < R; i++) asm volatile("" : "+f"(d[i])::"memory");
}
__device__ __forceinline__ uint64_t mkdesc(uint32_t addr, uint32_t lbo, uint32_t sbo, uint32_t sw) {
  return (uint64_t)((addr & 0x3FFFF) >> 4) | ((uint64_t)(lbo >> 4) << 16) | ((uint64_t)(sbo >> 4) << 32) | ((uint64_t)sw << 62);
}
__device__ __forceinline__ void bar_sync(int id, int n) { asm volatile("bar.sync %0, %1;" ::"r"(id), "r"(n) : "memory"); }
__device__ __forceinline__ void bar_arrive(int id, int n) { asm volatile("bar.arrive %0, %1;" ::"r"(id), "r"(n) : "memory"); }
__device__ __forceinline__ void fence_gpu() { asm volatile("fence.acq_rel.gpu;" ::: "memory"); }
__device__ __forceinline__ void fence_async_smem() { asm volatile("fence.proxy.async.shared::cta;" ::: "memory"); }
__device__ __forceinline__ void fence_async_global() { asm volatile("fence.proxy.async.global;" ::: "memory"); }
__device__ __forceinline__ unsigned ld_acquire(const unsigned* p) { unsigned v; asm volatile("ld.acquire.gpu.global.u32 %0, [%1];" : "=r"(v) : "l"(p) : "memory"); return v; }
__device__ __forceinline__ void red_release(unsigned* p) { asm volatile("red.release.gpu.global.add.u32 [%0], 1;" ::"l"(p) : "memory"); }
__device__ __forceinline__ void poll_ge(const unsigned* p, unsigned target) {
  asm volatile("{\n.reg .pred p;\n.reg .u32 c, v;\nmov.u32 c, 0;\nPL:\nld.relaxed.gpu.global.u32 v, [%0];\nsub.u32 v, v, %1;\nsetp.ge.s32 p, v, 0;\n@p bra PD;\nadd.u32 c, c, 1;\nsetp.lt.u32 p, c, 262144;\n@p bra PL;\nPD:\nfence.acquire.gpu;\n}" ::"l"(p), "r"(target) : "memory");
}
__device__ __forceinline__ uint32_t pack_bf16(float lo, float hi) { uint32_t r; asm("cvt.rn.bf16x2.f32 %0, %1, %2;" : "=r"(r) : "f"(hi), "f"(lo)); return r; }
__device__ __forceinline__ float bf_lo(uint32_t v) { return __uint_as_float(v << 16); }
__device__ __forceinline__ float bf_hi(uint32_t v) { return __uint_as_float(v & 0xffff0000u); }
__device__ __forceinline__ float ex2(float x) { float y; asm("ex2.approx.ftz.f32 %0, %1;" : "=f"(y) : "f"(x)); return y; }
__device__ __forceinline__ float rcp(float x) { float y; asm("rcp.approx.ftz.f32 %0, %1;" : "=f"(y) : "f"(x)); return y; }
__device__ __forceinline__ float silu_half(float h) { float y; asm("tanh.approx.f32 %0, %1;" : "=f"(y) : "f"(h)); return fmaf(h, y, h); }
__device__ __forceinline__ float2 lds64f(uint32_t a) { float2 v; asm volatile("ld.shared.v2.f32 {%0,%1}, [%2];" : "=f"(v.x), "=f"(v.y) : "r"(a) : "memory"); return v; }
__device__ __forceinline__ uint4 lds128(uint32_t a) { uint4 v; asm volatile("ld.shared.v4.u32 {%0,%1,%2,%3}, [%4];" : "=r"(v.x), "=r"(v.y), "=r"(v.z), "=r"(v.w) : "r"(a) : "memory"); return v; }
__device__ __forceinline__ void sts128(uint32_t a, uint32_t x, uint32_t y, uint32_t z, uint32_t w) { asm volatile("st.shared.v4.u32 [%0], {%1,%2,%3,%4};" ::"r"(a), "r"(x), "r"(y), "r"(z), "r"(w) : "memory"); }
__device__ __forceinline__ void sts32(uint32_t a, uint32_t x) { asm volatile("st.shared.u32 [%0], %1;" ::"r"(a), "r"(x) : "memory"); }
__device__ __forceinline__ void sts32f(uint32_t a, float x) { asm volatile("st.shared.f32 [%0], %1;" ::"r"(a), "f"(x) : "memory"); }
__device__ __forceinline__ void sts64f(uint32_t a, float x, float y) { asm volatile("st.shared.v2.f32 [%0], {%1,%2};" ::"r"(a), "f"(x), "f"(y) : "memory"); }
__device__ __forceinline__ float lds32f(uint32_t a) { float v; asm volatile("ld.shared.f32 %0, [%1];" : "=f"(v) : "r"(a) : "memory"); return v; }
__device__ __forceinline__ void sts16(uint32_t a, uint16_t x) { asm volatile("st.shared.u16 [%0], %1;" ::"r"(a), "h"(x) : "memory"); }
__device__ __forceinline__ void stsm4(uint32_t a, uint32_t r0, uint32_t r1, uint32_t r2, uint32_t r3) {
  asm volatile("stmatrix.sync.aligned.m8n8.x4.shared.b16 [%0], {%1,%2,%3,%4};" ::"r"(a), "r"(r0), "r"(r1), "r"(r2), "r"(r3) : "memory");
}
__device__ __forceinline__ void ldsm4t(uint32_t a, uint32_t& r0, uint32_t& r1, uint32_t& r2, uint32_t& r3) {
  asm volatile("ldmatrix.sync.aligned.m8n8.x4.trans.shared.b16 {%0,%1,%2,%3}, [%4];" : "=r"(r0), "=r"(r1), "=r"(r2), "=r"(r3) : "r"(a) : "memory");
}
__device__ __forceinline__ void ldsm2t(uint32_t a, uint32_t& r0, uint32_t& r1) {
  asm volatile("ldmatrix.sync.aligned.m8n8.x2.trans.shared.b16 {%0,%1}, [%2];" : "=r"(r0), "=r"(r1) : "r"(a) : "memory");
}
__device__ __forceinline__ void ldsm4(uint32_t a, uint32_t& r0, uint32_t& r1, uint32_t& r2, uint32_t& r3) {
  asm volatile("ldmatrix.sync.aligned.m8n8.x4.shared.b16 {%0,%1,%2,%3}, [%4];" : "=r"(r0), "=r"(r1), "=r"(r2), "=r"(r3) : "r"(a) : "memory");
}
__device__ __forceinline__ void ldsm2(uint32_t a, uint32_t& r0, uint32_t& r1) {
  asm volatile("ldmatrix.sync.aligned.m8n8.x2.shared.b16 {%0,%1}, [%2];" : "=r"(r0), "=r"(r1) : "r"(a) : "memory");
}
__device__ __forceinline__ void mma1688(float (&c)[4], uint32_t a0, uint32_t a1, uint32_t b0) {
  asm("mma.sync.aligned.m16n8k8.row.col.f32.bf16.bf16.f32 {%0,%1,%2,%3}, {%4,%5}, {%6}, {%0,%1,%2,%3};"
      : "+f"(c[0]), "+f"(c[1]), "+f"(c[2]), "+f"(c[3]) : "r"(a0), "r"(a1), "r"(b0));
}
__device__ __forceinline__ void mma1688z(float (&c)[4], uint32_t a0, uint32_t a1, uint32_t b0) {
  asm volatile("mma.sync.aligned.m16n8k8.row.col.f32.bf16.bf16.f32 {%0,%1,%2,%3}, {%4,%5}, {%6}, {%7,%7,%7,%7};"
      : "=f"(c[0]), "=f"(c[1]), "=f"(c[2]), "=f"(c[3]) : "r"(a0), "r"(a1), "r"(b0), "f"(0.f) : "memory");
}
__device__ __forceinline__ void mma16816v(float (&c)[4], uint32_t a0, uint32_t a1, uint32_t a2, uint32_t a3, uint32_t b0, uint32_t b1) {
  asm volatile("mma.sync.aligned.m16n8k16.row.col.f32.bf16.bf16.f32 {%0,%1,%2,%3}, {%4,%5,%6,%7}, {%8,%9}, {%0,%1,%2,%3};"
               : "+f"(c[0]), "+f"(c[1]), "+f"(c[2]), "+f"(c[3]) : "r"(a0), "r"(a1), "r"(a2), "r"(a3), "r"(b0), "r"(b1) : "memory");
}
__device__ __forceinline__ void mma16816(float (&c)[4], uint32_t a0, uint32_t a1, uint32_t a2, uint32_t a3, uint32_t b0, uint32_t b1) {
  asm("mma.sync.aligned.m16n8k16.row.col.f32.bf16.bf16.f32 {%0,%1,%2,%3}, {%4,%5,%6,%7}, {%8,%9}, {%0,%1,%2,%3};"
               : "+f"(c[0]), "+f"(c[1]), "+f"(c[2]), "+f"(c[3]) : "r"(a0), "r"(a1), "r"(a2), "r"(a3), "r"(b0), "r"(b1));
}
__device__ __forceinline__ uint4 ldg_nc128(const void* p) { uint4 v; asm volatile("ld.global.nc.L1::no_allocate.v4.u32 {%0,%1,%2,%3}, [%4];" : "=r"(v.x), "=r"(v.y), "=r"(v.z), "=r"(v.w) : "l"(p)); return v; }
__device__ __forceinline__ uint2 ldg_nc64(const void* p) { uint2 v; asm volatile("ld.global.nc.v2.u32 {%0,%1}, [%2];" : "=r"(v.x), "=r"(v.y) : "l"(p)); return v; }
__device__ __forceinline__ uint32_t ldg_nc32(const void* p) { uint32_t v; asm volatile("ld.global.nc.u32 %0, [%1];" : "=r"(v) : "l"(p)); return v; }
__device__ __forceinline__ float4 ldg_cg128f(const void* p) { float4 v; asm volatile("ld.global.cg.v4.f32 {%0,%1,%2,%3}, [%4];" : "=f"(v.x), "=f"(v.y), "=f"(v.z), "=f"(v.w) : "l"(p) : "memory"); return v; }
__device__ __forceinline__ float2 ldg_cg64f(const void* p) { float2 v; asm volatile("ld.global.cg.v2.f32 {%0,%1}, [%2];" : "=f"(v.x), "=f"(v.y) : "l"(p) : "memory"); return v; }
__device__ __forceinline__ uint4 ld_relaxed128(const void* p) { uint4 v; asm volatile("ld.relaxed.gpu.global.v4.u32 {%0,%1,%2,%3}, [%4];" : "=r"(v.x), "=r"(v.y), "=r"(v.z), "=r"(v.w) : "l"(p) : "memory"); return v; }
__device__ __forceinline__ void st_relaxed128(void* p, uint32_t a, uint32_t b, uint32_t c, uint32_t d) { asm volatile("st.relaxed.gpu.global.v4.u32 [%0], {%1,%2,%3,%4};" ::"l"(p), "r"(a), "r"(b), "r"(c), "r"(d) : "memory"); }
__device__ __forceinline__ void stg32(void* p, uint32_t v) { asm volatile("st.global.u32 [%0], %1;" ::"l"(p), "r"(v) : "memory"); }
__device__ __forceinline__ void stg128f(void* p, float a, float b, float c, float d) { asm volatile("st.global.v4.f32 [%0], {%1,%2,%3,%4};" ::"l"(p), "f"(a), "f"(b), "f"(c), "f"(d) : "memory"); }

__device__ __forceinline__ void wgmma_ss(float (&d)[40], uint64_t da, uint64_t db, int sd) {
  asm volatile("{\n.reg .pred p;\nsetp.ne.b32 p, %42, 0;\nwgmma.mma_async.sync.aligned.m64n80k16.f32.bf16.bf16 {%0, %1, %2, %3, %4, %5, %6, %7, %8, %9, %10, %11, %12, %13, %14, %15, %16, %17, %18, %19, %20, %21, %22, %23, %24, %25, %26, %27, %28, %29, %30, %31, %32, %33, %34, %35, %36, %37, %38, %39}, %40, %41, p, 1, 1, 0, 1;\n}"
    : "+f"(d[0]), "+f"(d[1]), "+f"(d[2]), "+f"(d[3]), "+f"(d[4]), "+f"(d[5]), "+f"(d[6]), "+f"(d[7]), "+f"(d[8]), "+f"(d[9]), "+f"(d[10]), "+f"(d[11]), "+f"(d[12]), "+f"(d[13]), "+f"(d[14]), "+f"(d[15]), "+f"(d[16]), "+f"(d[17]), "+f"(d[18]), "+f"(d[19]), "+f"(d[20]), "+f"(d[21]), "+f"(d[22]), "+f"(d[23]), "+f"(d[24]), "+f"(d[25]), "+f"(d[26]), "+f"(d[27]), "+f"(d[28]), "+f"(d[29]), "+f"(d[30]), "+f"(d[31]), "+f"(d[32]), "+f"(d[33]), "+f"(d[34]), "+f"(d[35]), "+f"(d[36]), "+f"(d[37]), "+f"(d[38]), "+f"(d[39]) : "l"(da), "l"(db), "r"(sd));
}
__device__ __forceinline__ void wgmma_ss(float (&d)[44], uint64_t da, uint64_t db, int sd) {
  asm volatile("{\n.reg .pred p;\nsetp.ne.b32 p, %46, 0;\nwgmma.mma_async.sync.aligned.m64n88k16.f32.bf16.bf16 {%0, %1, %2, %3, %4, %5, %6, %7, %8, %9, %10, %11, %12, %13, %14, %15, %16, %17, %18, %19, %20, %21, %22, %23, %24, %25, %26, %27, %28, %29, %30, %31, %32, %33, %34, %35, %36, %37, %38, %39, %40, %41, %42, %43}, %44, %45, p, 1, 1, 0, 1;\n}"
    : "+f"(d[0]), "+f"(d[1]), "+f"(d[2]), "+f"(d[3]), "+f"(d[4]), "+f"(d[5]), "+f"(d[6]), "+f"(d[7]), "+f"(d[8]), "+f"(d[9]), "+f"(d[10]), "+f"(d[11]), "+f"(d[12]), "+f"(d[13]), "+f"(d[14]), "+f"(d[15]), "+f"(d[16]), "+f"(d[17]), "+f"(d[18]), "+f"(d[19]), "+f"(d[20]), "+f"(d[21]), "+f"(d[22]), "+f"(d[23]), "+f"(d[24]), "+f"(d[25]), "+f"(d[26]), "+f"(d[27]), "+f"(d[28]), "+f"(d[29]), "+f"(d[30]), "+f"(d[31]), "+f"(d[32]), "+f"(d[33]), "+f"(d[34]), "+f"(d[35]), "+f"(d[36]), "+f"(d[37]), "+f"(d[38]), "+f"(d[39]), "+f"(d[40]), "+f"(d[41]), "+f"(d[42]), "+f"(d[43]) : "l"(da), "l"(db), "r"(sd));
}
__device__ __forceinline__ void wgmma_ss(float (&d)[64], uint64_t da, uint64_t db, int sd) {
  asm volatile("{\n.reg .pred p;\nsetp.ne.b32 p, %66, 0;\nwgmma.mma_async.sync.aligned.m64n128k16.f32.bf16.bf16 {%0, %1, %2, %3, %4, %5, %6, %7, %8, %9, %10, %11, %12, %13, %14, %15, %16, %17, %18, %19, %20, %21, %22, %23, %24, %25, %26, %27, %28, %29, %30, %31, %32, %33, %34, %35, %36, %37, %38, %39, %40, %41, %42, %43, %44, %45, %46, %47, %48, %49, %50, %51, %52, %53, %54, %55, %56, %57, %58, %59, %60, %61, %62, %63}, %64, %65, p, 1, 1, 0, 1;\n}"
    : "+f"(d[0]), "+f"(d[1]), "+f"(d[2]), "+f"(d[3]), "+f"(d[4]), "+f"(d[5]), "+f"(d[6]), "+f"(d[7]), "+f"(d[8]), "+f"(d[9]), "+f"(d[10]), "+f"(d[11]), "+f"(d[12]), "+f"(d[13]), "+f"(d[14]), "+f"(d[15]), "+f"(d[16]), "+f"(d[17]), "+f"(d[18]), "+f"(d[19]), "+f"(d[20]), "+f"(d[21]), "+f"(d[22]), "+f"(d[23]), "+f"(d[24]), "+f"(d[25]), "+f"(d[26]), "+f"(d[27]), "+f"(d[28]), "+f"(d[29]), "+f"(d[30]), "+f"(d[31]), "+f"(d[32]), "+f"(d[33]), "+f"(d[34]), "+f"(d[35]), "+f"(d[36]), "+f"(d[37]), "+f"(d[38]), "+f"(d[39]), "+f"(d[40]), "+f"(d[41]), "+f"(d[42]), "+f"(d[43]), "+f"(d[44]), "+f"(d[45]), "+f"(d[46]), "+f"(d[47]), "+f"(d[48]), "+f"(d[49]), "+f"(d[50]), "+f"(d[51]), "+f"(d[52]), "+f"(d[53]), "+f"(d[54]), "+f"(d[55]), "+f"(d[56]), "+f"(d[57]), "+f"(d[58]), "+f"(d[59]), "+f"(d[60]), "+f"(d[61]), "+f"(d[62]), "+f"(d[63]) : "l"(da), "l"(db), "r"(sd));
}
__device__ __forceinline__ void wgmma_ss(float (&d)[80], uint64_t da, uint64_t db, int sd) {
  asm volatile("{\n.reg .pred p;\nsetp.ne.b32 p, %82, 0;\nwgmma.mma_async.sync.aligned.m64n160k16.f32.bf16.bf16 {%0, %1, %2, %3, %4, %5, %6, %7, %8, %9, %10, %11, %12, %13, %14, %15, %16, %17, %18, %19, %20, %21, %22, %23, %24, %25, %26, %27, %28, %29, %30, %31, %32, %33, %34, %35, %36, %37, %38, %39, %40, %41, %42, %43, %44, %45, %46, %47, %48, %49, %50, %51, %52, %53, %54, %55, %56, %57, %58, %59, %60, %61, %62, %63, %64, %65, %66, %67, %68, %69, %70, %71, %72, %73, %74, %75, %76, %77, %78, %79}, %80, %81, p, 1, 1, 0, 1;\n}"
    : "+f"(d[0]), "+f"(d[1]), "+f"(d[2]), "+f"(d[3]), "+f"(d[4]), "+f"(d[5]), "+f"(d[6]), "+f"(d[7]), "+f"(d[8]), "+f"(d[9]), "+f"(d[10]), "+f"(d[11]), "+f"(d[12]), "+f"(d[13]), "+f"(d[14]), "+f"(d[15]), "+f"(d[16]), "+f"(d[17]), "+f"(d[18]), "+f"(d[19]), "+f"(d[20]), "+f"(d[21]), "+f"(d[22]), "+f"(d[23]), "+f"(d[24]), "+f"(d[25]), "+f"(d[26]), "+f"(d[27]), "+f"(d[28]), "+f"(d[29]), "+f"(d[30]), "+f"(d[31]), "+f"(d[32]), "+f"(d[33]), "+f"(d[34]), "+f"(d[35]), "+f"(d[36]), "+f"(d[37]), "+f"(d[38]), "+f"(d[39]), "+f"(d[40]), "+f"(d[41]), "+f"(d[42]), "+f"(d[43]), "+f"(d[44]), "+f"(d[45]), "+f"(d[46]), "+f"(d[47]), "+f"(d[48]), "+f"(d[49]), "+f"(d[50]), "+f"(d[51]), "+f"(d[52]), "+f"(d[53]), "+f"(d[54]), "+f"(d[55]), "+f"(d[56]), "+f"(d[57]), "+f"(d[58]), "+f"(d[59]), "+f"(d[60]), "+f"(d[61]), "+f"(d[62]), "+f"(d[63]), "+f"(d[64]), "+f"(d[65]), "+f"(d[66]), "+f"(d[67]), "+f"(d[68]), "+f"(d[69]), "+f"(d[70]), "+f"(d[71]), "+f"(d[72]), "+f"(d[73]), "+f"(d[74]), "+f"(d[75]), "+f"(d[76]), "+f"(d[77]), "+f"(d[78]), "+f"(d[79]) : "l"(da), "l"(db), "r"(sd));
}
__device__ __forceinline__ void wgmma_rs(float (&d)[40], uint32_t a0, uint32_t a1, uint32_t a2, uint32_t a3, uint64_t db, int sd) {
  asm volatile("{\n.reg .pred p;\nsetp.ne.b32 p, %45, 0;\nwgmma.mma_async.sync.aligned.m64n80k16.f32.bf16.bf16 {%0, %1, %2, %3, %4, %5, %6, %7, %8, %9, %10, %11, %12, %13, %14, %15, %16, %17, %18, %19, %20, %21, %22, %23, %24, %25, %26, %27, %28, %29, %30, %31, %32, %33, %34, %35, %36, %37, %38, %39}, {%40, %41, %42, %43}, %44, p, 1, 1, 1;\n}"
    : "+f"(d[0]), "+f"(d[1]), "+f"(d[2]), "+f"(d[3]), "+f"(d[4]), "+f"(d[5]), "+f"(d[6]), "+f"(d[7]), "+f"(d[8]), "+f"(d[9]), "+f"(d[10]), "+f"(d[11]), "+f"(d[12]), "+f"(d[13]), "+f"(d[14]), "+f"(d[15]), "+f"(d[16]), "+f"(d[17]), "+f"(d[18]), "+f"(d[19]), "+f"(d[20]), "+f"(d[21]), "+f"(d[22]), "+f"(d[23]), "+f"(d[24]), "+f"(d[25]), "+f"(d[26]), "+f"(d[27]), "+f"(d[28]), "+f"(d[29]), "+f"(d[30]), "+f"(d[31]), "+f"(d[32]), "+f"(d[33]), "+f"(d[34]), "+f"(d[35]), "+f"(d[36]), "+f"(d[37]), "+f"(d[38]), "+f"(d[39]) : "r"(a0), "r"(a1), "r"(a2), "r"(a3), "l"(db), "r"(sd));
}
__device__ __forceinline__ void wgmma_rs0(float (&d)[40], uint32_t a0, uint32_t a1, uint32_t a2, uint32_t a3, uint64_t db) {
  asm volatile("{\n.reg .pred p;\nsetp.ne.b32 p, 0, 0;\nwgmma.mma_async.sync.aligned.m64n80k16.f32.bf16.bf16 {%0, %1, %2, %3, %4, %5, %6, %7, %8, %9, %10, %11, %12, %13, %14, %15, %16, %17, %18, %19, %20, %21, %22, %23, %24, %25, %26, %27, %28, %29, %30, %31, %32, %33, %34, %35, %36, %37, %38, %39}, {%40, %41, %42, %43}, %44, p, 1, 1, 1;\n}"
    : "=f"(d[0]), "=f"(d[1]), "=f"(d[2]), "=f"(d[3]), "=f"(d[4]), "=f"(d[5]), "=f"(d[6]), "=f"(d[7]), "=f"(d[8]), "=f"(d[9]), "=f"(d[10]), "=f"(d[11]), "=f"(d[12]), "=f"(d[13]), "=f"(d[14]), "=f"(d[15]), "=f"(d[16]), "=f"(d[17]), "=f"(d[18]), "=f"(d[19]), "=f"(d[20]), "=f"(d[21]), "=f"(d[22]), "=f"(d[23]), "=f"(d[24]), "=f"(d[25]), "=f"(d[26]), "=f"(d[27]), "=f"(d[28]), "=f"(d[29]), "=f"(d[30]), "=f"(d[31]), "=f"(d[32]), "=f"(d[33]), "=f"(d[34]), "=f"(d[35]), "=f"(d[36]), "=f"(d[37]), "=f"(d[38]), "=f"(d[39]) : "r"(a0), "r"(a1), "r"(a2), "r"(a3), "l"(db));
}
__device__ __forceinline__ void wgmma_rs(float (&d)[48], uint32_t a0, uint32_t a1, uint32_t a2, uint32_t a3, uint64_t db, int sd) {
  asm volatile("{\n.reg .pred p;\nsetp.ne.b32 p, %53, 0;\nwgmma.mma_async.sync.aligned.m64n96k16.f32.bf16.bf16 {%0, %1, %2, %3, %4, %5, %6, %7, %8, %9, %10, %11, %12, %13, %14, %15, %16, %17, %18, %19, %20, %21, %22, %23, %24, %25, %26, %27, %28, %29, %30, %31, %32, %33, %34, %35, %36, %37, %38, %39, %40, %41, %42, %43, %44, %45, %46, %47}, {%48, %49, %50, %51}, %52, p, 1, 1, 0;\n}"
    : "+f"(d[0]), "+f"(d[1]), "+f"(d[2]), "+f"(d[3]), "+f"(d[4]), "+f"(d[5]), "+f"(d[6]), "+f"(d[7]), "+f"(d[8]), "+f"(d[9]), "+f"(d[10]), "+f"(d[11]), "+f"(d[12]), "+f"(d[13]), "+f"(d[14]), "+f"(d[15]), "+f"(d[16]), "+f"(d[17]), "+f"(d[18]), "+f"(d[19]), "+f"(d[20]), "+f"(d[21]), "+f"(d[22]), "+f"(d[23]), "+f"(d[24]), "+f"(d[25]), "+f"(d[26]), "+f"(d[27]), "+f"(d[28]), "+f"(d[29]), "+f"(d[30]), "+f"(d[31]), "+f"(d[32]), "+f"(d[33]), "+f"(d[34]), "+f"(d[35]), "+f"(d[36]), "+f"(d[37]), "+f"(d[38]), "+f"(d[39]), "+f"(d[40]), "+f"(d[41]), "+f"(d[42]), "+f"(d[43]), "+f"(d[44]), "+f"(d[45]), "+f"(d[46]), "+f"(d[47]) : "r"(a0), "r"(a1), "r"(a2), "r"(a3), "l"(db), "r"(sd));
}
__device__ __forceinline__ void wgmma_rs0(float (&d)[48], uint32_t a0, uint32_t a1, uint32_t a2, uint32_t a3, uint64_t db) {
  asm volatile("{\n.reg .pred p;\nsetp.ne.b32 p, 0, 0;\nwgmma.mma_async.sync.aligned.m64n96k16.f32.bf16.bf16 {%0, %1, %2, %3, %4, %5, %6, %7, %8, %9, %10, %11, %12, %13, %14, %15, %16, %17, %18, %19, %20, %21, %22, %23, %24, %25, %26, %27, %28, %29, %30, %31, %32, %33, %34, %35, %36, %37, %38, %39, %40, %41, %42, %43, %44, %45, %46, %47}, {%48, %49, %50, %51}, %52, p, 1, 1, 0;\n}"
    : "=f"(d[0]), "=f"(d[1]), "=f"(d[2]), "=f"(d[3]), "=f"(d[4]), "=f"(d[5]), "=f"(d[6]), "=f"(d[7]), "=f"(d[8]), "=f"(d[9]), "=f"(d[10]), "=f"(d[11]), "=f"(d[12]), "=f"(d[13]), "=f"(d[14]), "=f"(d[15]), "=f"(d[16]), "=f"(d[17]), "=f"(d[18]), "=f"(d[19]), "=f"(d[20]), "=f"(d[21]), "=f"(d[22]), "=f"(d[23]), "=f"(d[24]), "=f"(d[25]), "=f"(d[26]), "=f"(d[27]), "=f"(d[28]), "=f"(d[29]), "=f"(d[30]), "=f"(d[31]), "=f"(d[32]), "=f"(d[33]), "=f"(d[34]), "=f"(d[35]), "=f"(d[36]), "=f"(d[37]), "=f"(d[38]), "=f"(d[39]), "=f"(d[40]), "=f"(d[41]), "=f"(d[42]), "=f"(d[43]), "=f"(d[44]), "=f"(d[45]), "=f"(d[46]), "=f"(d[47]) : "r"(a0), "r"(a1), "r"(a2), "r"(a3), "l"(db));
}

#define CLUSTER_ARRIVE() asm volatile("barrier.cluster.arrive.relaxed.aligned;" ::: "memory")
#define CLUSTER_WAIT() asm volatile("barrier.cluster.wait.aligned;" ::: "memory")

__device__ __forceinline__ void ring_item(uint32_t dst, const CUtensorMap* m0, int col, int row, uint32_t bar, uint32_t bytes) {
  mbar_expect_tx(bar, bytes);
  tma3d_mc(dst, m0, col, row, bar);
  tma2d_mc(dst + 4096, m0 + 1, col + 64, row, bar);
}

struct Rel {
  uint32_t base; bool on;
  __device__ __forceinline__ Rel(uint32_t sb, int tid) {
    asm volatile("mapa.shared::cluster.u32 %0, %1, %2;" : "=r"(base) : "r"(sb), "r"((tid >> 5) & 1));
    on = (tid & 95) == 0;
  }
  __device__ __forceinline__ void operator()(uint32_t off) const {
    if (on) asm volatile("mbarrier.arrive.shared::cluster.b64 _, [%0];" ::"r"(base + off) : "memory");
  }
};

template <int R>
__device__ __forceinline__ void tile_loop(float (&a0)[R], float (&a1)[R], uint32_t sb, uint32_t fbar, uint32_t& ph, uint32_t& so, int k0, int k1,
                                          const Rel& rel, uint32_t& prev_r, uint32_t& prev_x, uint32_t xrel_step, int ksig, int sid, uint32_t clk0) {
  uint64_t da = mkdesc(sb + k0 * 16384, 16, 1024, 1);
  const uint64_t db0 = mkdesc(sb + RING_OFF, 2048, 512, 2);
  uint32_t cur_x = xrel_step ? BAR_X + 8 * k0 : BAR_DUMMY;
#pragma unroll 1
  for (int k = k0; k < k1; k++) {
    const uint64_t db = db0 + so * (SLOT / 128);
    mbar_wait(sb + fbar + 24 + so, (ph >> so) & 1);
    STAMP2_IF((threadIdx.x & 127) == 0, sid + k);
    wg_fence();
    wgmma_ss(a0, da, db, k); wgmma_ss(a1, da + 512, db, k);
    wg_commit();
    wg_wait<1>();
    rel(prev_r); rel(prev_x);
    if (k == ksig) bar_arrive(15, 256);
    wgmma_ss(a0, da + 2, db + 64, 1); wgmma_ss(a1, da + 514, db + 64, 1);
    wgmma_ss(a0, da + 4, db + 384, 1); wgmma_ss(a1, da + 516, db + 384, 1);
    wgmma_ss(a0, da + 6, db + 448, 1); wgmma_ss(a1, da + 518, db + 448, 1);
    wg_commit();
    ph ^= 1u << so;
    prev_r = BAR_RE + 24 + so; prev_x = cur_x; cur_x += xrel_step;
    so = (so + 8) & 24; da += 1024;
  }
}

__device__ __forceinline__ void fetch_cs(uint32_t sb, int c, int lane, unsigned tag, int u0, int u1) {
  const int ua = u0 + lane, ub = min(u0 + 32 + lane, u1 - 1);
  uint4 va, vb;
#pragma unroll 1
  for (int tries = 0; tries < (1 << 16); tries++) {
    va = ld_relaxed128(g_colsum + c * 228 + ua); vb = ld_relaxed128(g_colsum + c * 228 + ub);
    if (va.y == tag && va.w == tag && vb.y == tag && vb.w == tag) break;
  }
  sts64f(sb + CS_OFF + ua * 8, __uint_as_float(va.x), __uint_as_float(va.z));
  sts64f(sb + CS_OFF + ub * 8, __uint_as_float(vb.x), __uint_as_float(vb.z));
}

__device__ __forceinline__ void build_kvb(uint32_t sb, int c, int half, int lane) {
  const int g = lane >> 2, t = lane & 3;
  mbar_wait(sb + BAR_X + 8 * 9, 1);
#pragma unroll 1
  for (int i = 0; i < 30; i++) sts128(sb + KVB_OFF + (half * 960 + i * 32 + lane) * 16, 0u, 0u, 0u, 0u);
  bar_sync(3, 64);
#pragma unroll 1
  for (int h = 2 * half; h < 2 * half + 2; h++) {
    uint4 v[10];
#pragma unroll 1
    for (int tries = 0; tries < (1 << 16); tries++) {
      uint32_t bad = 0;
#pragma unroll
      for (int i = 0; i < 10; i++) v[i] = ld_relaxed128(g_kv + (c * 4 + h) * 320 + i * 32 + lane);
#pragma unroll
      for (int i = 0; i < 10; i++) bad |= v[i].w ^ 0x41800000u;
      if (__all_sync(0xffffffffu, bad == 0)) break;
    }
    const int nb = (5 * h) >> 1, odd = h & 1;
    const uint32_t ca = sb + CS_OFF + (CS_V + nb * 8 + g) * 4;
    const float c0 = lds32f(ca), c1 = lds32f(ca + 32), c2 = lds32f(ca + 64);
    const uint32_t base = sb + KVB_OFF + t * 1536 + h * 4;
    const uint32_t dump = sb + KVB_OFF + 30720 + lane * 4;
    const uint32_t p1 = base + (nb + 1) * 128 + g * 16;
    const bool v0 = !odd || g >= 4, v2 = odd || g < 4;
#pragma unroll
    for (int nf = 0; nf < 5; nf++) {
      const uint32_t s0 = odd ? v[2 * nf].x : v[2 * nf].z, s1 = odd ? v[2 * nf + 1].x : v[2 * nf + 1].z;
      const float m0 = __uint_as_float(__shfl_sync(0xffffffffu, s0, (odd ? 4 : 20) + t)), m1 = __uint_as_float(__shfl_sync(0xffffffffu, s1, (odd ? 4 : 20) + t));
      const uint32_t z = __shfl_sync(0xffffffffu, pack_bf16(__uint_as_float(s0), __uint_as_float(s1)), (odd ? 0 : 16) + t);
      sts32(v0 ? p1 - 128 + nf * 6144 : dump, pack_bf16(fmaf(-c0, m0, __uint_as_float(v[2 * nf].x)), fmaf(-c0, m1, __uint_as_float(v[2 * nf + 1].x))));
      sts32(p1 + nf * 6144, pack_bf16(fmaf(-c1, m0, __uint_as_float(v[2 * nf].y)), fmaf(-c1, m1, __uint_as_float(v[2 * nf + 1].y))));
      sts32(v2 ? p1 + 128 + nf * 6144 : dump, pack_bf16(fmaf(-c2, m0, __uint_as_float(v[2 * nf].z)), fmaf(-c2, m1, __uint_as_float(v[2 * nf + 1].z))));
      sts32(g < 4 ? base + (10 + (h >> 1)) * 128 + (2 * g + odd) * 16 + nf * 6144 : dump, z);
    }
  }
  fence_async_smem();
  __syncwarp();
  if (lane == 0) mbar_arrive_n(sb + BAR_X + 8 * 11, NCTA_MC);
}

struct RowStats { float mean[2][2], rstd[2][2]; };
__device__ __forceinline__ void load_stats(RowStats& st, uint32_t sb, int w, int g) {
#pragma unroll
  for (int m = 0; m < 2; m++)
#pragma unroll
    for (int i = 0; i < 2; i++) {
      float2 v = lds64f(sb + ST_OFF + (64 * m + 16 * w + 8 * i + g) * 8);
      st.mean[m][i] = v.x; st.rstd[m][i] = v.y;
    }
}

template <int R>
__device__ __forceinline__ void epi_h(float (&a0)[R], float (&a1)[R], uint32_t (&o)[R], uint32_t sb, int cs_off, int w, int lane, uint32_t zero) {
  RowStats st; load_stats(st, sb, w, lane >> 2);
#pragma unroll
  for (int m = 0; m < 2; m++) { st.rstd[m][0] *= 0.5f; st.rstd[m][1] *= 0.5f; }
  const uint32_t ca = sb + CS_OFF + (cs_off + 2 * (lane & 3)) * 4;
#pragma unroll
  for (int j = 0; j < R / 4; j++) {
    const int d = j >= E1_DIST ? 4 * (j - E1_DIST) : 0;
    const float2 cs = lds64f((j >= E1_DIST ? (ca | (o[d] & o[d + 1] & o[d + 2] & o[d + 3] & zero)) : ca) + j * 32);
#pragma unroll
    for (int i = 0; i < 2; i++) {
      o[4 * j + i] = pack_bf16(silu_half(fmaf(-st.mean[0][i], cs.x, a0[4 * j + 2 * i]) * st.rstd[0][i]), silu_half(fmaf(-st.mean[0][i], cs.y, a0[4 * j + 2 * i + 1]) * st.rstd[0][i]));
      o[4 * j + 2 + i] = pack_bf16(silu_half(fmaf(-st.mean[1][i], cs.x, a1[4 * j + 2 * i]) * st.rstd[1][i]), silu_half(fmaf(-st.mean[1][i], cs.y, a1[4 * j + 2 * i + 1]) * st.rstd[1][i]));
    }
  }
#pragma unroll
  for (int i = 0; i < R; i++) asm volatile("" : "+r"(o[i])::"memory");
}
template <int R, int I0, int I1>
__device__ __forceinline__ void store_h(const uint32_t (&o)[R], char* hp) {
#pragma unroll
  for (int i = I0; i < I1; i++) stg32(hp + (i >> 2) * 2048 + (i & 1) * 128 + ((i >> 1) & 1) * 1024, o[i]);
}

__device__ __forceinline__ void fix_pack(float (&a0)[40], float (&a1)[40], uint32_t (&f0)[20], uint32_t (&f1)[20], const RowStats& st, uint32_t cs_addr) {
#pragma unroll
  for (int j = 0; j < 10; j++) {
    float2 cs = lds64f(cs_addr + j * 32);
#pragma unroll
    for (int i = 0; i < 2; i++) {
      float u0 = fmaf(-st.mean[0][i], cs.x, a0[4 * j + 2 * i]), u1 = fmaf(-st.mean[0][i], cs.y, a0[4 * j + 2 * i + 1]);
      float u2 = fmaf(-st.mean[1][i], cs.x, a1[4 * j + 2 * i]), u3 = fmaf(-st.mean[1][i], cs.y, a1[4 * j + 2 * i + 1]);
      f0[2 * j + i] = pack_bf16(u0, u1);
      f1[2 * j + i] = pack_bf16(u2, u3);
    }
  }
}

__device__ __forceinline__ void phi_gemm(float (&p)[40], uint32_t (&f)[20], uint32_t sb) {
  uint64_t db = mkdesc(sb + WPHI_OFF, 1280, 128, 0);
#pragma unroll
  for (int kk = 0; kk < 5; kk++) {
    if (kk == 0) wgmma_rs0(p, f[0], f[1], f[2], f[3], db);
    else wgmma_rs(p, f[4 * kk], f[4 * kk + 1], f[4 * kk + 2], f[4 * kk + 3], db + kk * 160, 1);
  }
  wg_commit();
}

__device__ __forceinline__ void dual_softmax(const float (&p)[40], int i, float sc, uint32_t (&o)[20]) {
  float mx = p[2 * i], mn = p[2 * i], mx2 = p[2 * i + 1], mn2 = p[2 * i + 1];
#pragma unroll
  for (int j = 1; j < 10; j++) { mx = fmaxf(mx, p[4 * j + 2 * i]); mn = fminf(mn, p[4 * j + 2 * i]); mx2 = fmaxf(mx2, p[4 * j + 2 * i + 1]); mn2 = fminf(mn2, p[4 * j + 2 * i + 1]); }
  const float bp = -fmaxf(mx, mx2) * sc, bm = fminf(mn, mn2) * sc;
  float e[20];
#pragma unroll
  for (int j = 0; j < 10; j++) { e[2 * j] = ex2(fmaf(p[4 * j + 2 * i], sc, bp)); e[2 * j + 1] = ex2(fmaf(p[4 * j + 2 * i + 1], sc, bp)); }
  float s0 = e[0], s1 = e[1];
#pragma unroll
  for (int j = 1; j < 10; j++) { s0 += e[2 * j]; s1 += e[2 * j + 1]; }
  float r = rcp(s0 + s1);
#pragma unroll
  for (int j = 0; j < 10; j++) o[j] = pack_bf16(e[2 * j] * r, e[2 * j + 1] * r);
#pragma unroll
  for (int j = 0; j < 10; j++) { e[2 * j] = ex2(fmaf(p[4 * j + 2 * i], -sc, bm)); e[2 * j + 1] = ex2(fmaf(p[4 * j + 2 * i + 1], -sc, bm)); }
  s0 = e[0]; s1 = e[1];
#pragma unroll
  for (int j = 1; j < 10; j++) { s0 += e[2 * j]; s1 += e[2 * j + 1]; }
  r = rcp(s0 + s1);
#pragma unroll
  for (int j = 0; j < 10; j++) o[10 + j] = pack_bf16(e[2 * j] * r, e[2 * j + 1] * r);
}
__device__ __forceinline__ void store_phi(uint32_t a, const uint32_t (&o)[20]) {
#pragma unroll
  for (int v = 0; v < 5; v++) sts128(a + v * 16, o[4 * v], o[4 * v + 1], o[4 * v + 2], o[4 * v + 3]);
}

__global__ void __cluster_dims__(2, 1, 1) __launch_bounds__(384, 1)
fused_kernel(const __nv_bfloat16* __restrict__ x, const __nv_bfloat16* __restrict__ wqkv,
             const __nv_bfloat16* __restrict__ wphi, const __nv_bfloat16* __restrict__ w1, const __nv_bfloat16* __restrict__ w2,
             const __nv_bfloat16* __restrict__ wo, const __grid_constant__ Maps maps) {
  extern __shared__ __align__(1024) uint8_t smem_raw[];
  const uint32_t clk0 = (uint32_t)clock();
  const uint32_t sb = __shfl_sync(0xffffffffu, smem_u32(smem_raw), 0);
  const int warp = __shfl_sync(0xffffffffu, threadIdx.x >> 5, 0);
  const int lane = threadIdx.x & 31;
  if (warp < 10) {
    const int j = warp >= 8 ? warp - 8 : warp + 2;
    const uint32_t cnt = ((USE_MC ? 0x2211111444ull : 0x1111111222ull) >> (4 * j)) & 15;
    if (elect_one()) {
#pragma unroll
      for (int e = 0; e < 4; e++) mbar_init(sb + BAR_X + 32 * j + 8 * e, cnt);
      if (warp < 4) {
#pragma unroll
        for (int e = 0; e < 4; e++) mbar_init(sb + BAR_BE + 32 * warp + 8 * e, warp == 0 ? NCTA_MC : warp == 3 ? 1 : 2);
      }
      asm volatile("fence.mbarrier_init.release.cluster;" ::: "memory");
    }
    __syncwarp();
  }
  CLUSTER_ARRIVE();
  STAMP_IF(threadIdx.x == 256, 56);
  int lp;
  { const int i = blockIdx.x >> 1; lp = i < 4 ? 39 + 8 * i : i < 36 ? i - 4 : i < 64 ? 32 + ((i - 36) / 7) * 8 + (i - 36) % 7 : i; }
  const int bid = 2 * lp + (blockIdx.x & 1);
  if (bid >= 128) {
    const int e = bid - 128;
    CLUSTER_WAIT();
    const uint32_t fb = sb + CS_OFF, eb = fb + 96, red = sb + 12 * 16384;
    if (elect_one()) { mbar_init(fb + 8 * warp, 1); mbar_init(eb + 8 * warp, 8); asm volatile("fence.mbarrier_init.release.cluster;" ::: "memory"); }
    __syncthreads();
    if (warp == 8) {
      uint32_t s = 0, par = 1;
#pragma unroll 1
      for (int b = e; b < 57; b += 4) {
        const bool isw = b < 16 || (b >= 26 && b < 37);
        const int col = 64 * (b < 16 ? b : b < 26 ? b - 6 : b < 37 ? b - 10 : b < 47 ? b - 37 : b - 27);
#pragma unroll 1
        for (int row = 0; row < 640; row += 128) {
          mbar_wait(eb + 8 * s, par);
          if (elect_one()) { mbar_expect_tx(fb + 8 * s, 16384); tma2d(sb + s * 16384, isw ? &maps.jw : &maps.jq, col, row, fb + 8 * s); }
          if (++s == 12) { s = 0; par ^= 1; }
        }
      }
    } else if (warp < 8) {
      unsigned tag = 0;
      if (threadIdx.x == 0) { asm volatile("atom.relaxed.gpu.global.add.u32 %0, [%1], 32;" : "=r"(tag) : "l"(g_pro) : "memory"); sts32(red + 4096, (tag >> 8) + 1); }
      const int g = lane >> 2, t = lane & 3;
      const uint32_t sel0 = g == 0 ? 0x00003F80u : g == 1 ? 0x3F800000u : 0u, sel1 = g == 2 ? 0x00003F80u : g == 3 ? 0x3F800000u : 0u;
      const uint32_t a0 = sb + (16 * warp + 2 * t) * 128 + ((g ^ (2 * t)) << 4), a1 = sb + (16 * warp + 2 * t + 1) * 128 + ((g ^ (2 * t + 1)) << 4);
      uint32_t s = 0, par = 0, rb = 0;
#pragma unroll 1
      for (int b = e; b < 57; b += 4) {
        float c0[4] = {0.f, 0.f, 0.f, 0.f}, c1[4] = {0.f, 0.f, 0.f, 0.f};
#pragma unroll 1
        for (int i = 0; i < 5; i++) {
          mbar_wait(fb + 8 * s, par);
          const uint4 v0 = lds128(a0 + s * 16384), v1 = lds128(a1 + s * 16384), v2 = lds128(a0 + s * 16384 + 1024), v3 = lds128(a1 + s * 16384 + 1024);
          mma16816(c0, v0.x, v0.y, v0.z, v0.w, sel0, sel1); mma16816(c1, v1.x, v1.y, v1.z, v1.w, sel0, sel1);
          mma16816(c0, v2.x, v2.y, v2.z, v2.w, sel0, sel1); mma16816(c1, v3.x, v3.y, v3.z, v3.w, sel0, sel1);
          __syncwarp();
          if (lane == 0) mbar_arrive(eb + 8 * s);
          if (++s == 12) { s = 0; par ^= 1; }
        }
        if (t < 2) sts128(red + rb + (warp * 64 + g * 8 + 4 * t) * 4, __float_as_uint(c0[0] + c1[0]), __float_as_uint(c0[1] + c1[1]), __float_as_uint(c0[2] + c1[2]), __float_as_uint(c0[3] + c1[3]));
        bar_sync(1, 256);
        if (threadIdx.x < 64) {
          float sum = 0.f;
#pragma unroll
          for (int i = 0; i < 8; i++) sum += lds32f(red + rb + (i * 64 + threadIdx.x) * 4);
          int pos;
          if (b < 16) { const int n = 64 * b + threadIdx.x; pos = (n >> 7) * 456 + (n & 127); }
          else if (b >= 26 && b < 37) { const int n = 64 * (b - 26) + threadIdx.x, cc = n / 88; pos = cc * 456 + CS_W1B + (n - cc * 88); }
          else { const int n = 64 * (b < 26 ? b - 16 : b < 47 ? b - 37 : b - 47) + threadIdx.x, cc = n / 80; pos = cc * 456 + (b < 26 ? CS_K : b < 47 ? CS_Q : CS_V) + (n - cc * 80); }
          asm volatile("st.relaxed.gpu.global.v2.u32 [%0], {%1, %2};" ::"l"((uint2*)g_colsum + pos), "r"(__float_as_uint(sum)), "r"(__float_as_uint(lds32f(red + 4096))) : "memory");
        }
        rb ^= 2048;
      }
    }
    return;
  }
  const uint32_t rank = bid & 1;
  const int pair = bid >> 1;
  const int rg = pair & 7, c = pair >> 3;
  const int r = 2 * rg + rank;
  const int kap = c >> 2, jn = c & 3;

  if (warp >= 8) {
    asm volatile("setmaxnreg.dec.sync.aligned.u32 64;");
    if (warp == 8) {
      STAMP_IF(lane == 0, 57);
      if (elect_one()) {
        mbar_arrive_n(sb + BAR_X, 2 * NCTA_MC - 1);
        mbar_expect_tx(sb + BAR_X, 16384);
        tma2d(sb, &maps.x, 0, r * 128, sb + BAR_X);
      }
      __syncwarp();
      STAMP_IF(lane == 0, 58);
      CLUSTER_WAIT();
      {
        const uint32_t dst0 = sb + RING0 + (USE_MC ? rank * 6144 : 0);
        int rowa = 0, rowv = USE_MC ? rank * 32 : 0, kx = 1;
        const int cola = 128 * c + (USE_MC ? 64 * rank : 0), colv = 1280 + 80 * c;
        uint32_t mask = P1_MASK, xmask = P1_XMASK, id = 0, pm = 0xff;
#pragma unroll 1
        for (int i = 0; i < 24; i++) {
          const uint32_t dst = dst0 + id * SLOT;
          if (xmask & 1) {
            if (kx >= 7) mbar_wait(sb + BAR_RE + 8 * (kx - 7), 1);
            if (elect_one()) {
              mbar_arrive_n(sb + BAR_X + 8 * kx, 2 * NCTA_MC - 1);
              mbar_expect_tx(sb + BAR_X + 8 * kx, 16384);
              tma2d(sb + kx * 16384, &maps.x, kx * 64, r * 128, sb + BAR_X + 8 * kx);
            }
            kx++;
          }
          mbar_wait(sb + BAR_RE + 8 * id, (pm >> id) & 1);
          STAMP2_IF(lane == 0, 64 + i);
          if (mask & 1) {
            if (elect_one()) {
              mbar_expect_tx(sb + BAR_RF + 8 * id, 12288);
              tma2d_mc(dst, &maps.w1a, cola, rowa, sb + BAR_RF + 8 * id);
            }
            rowa = min(rowa + 48, 592);
          } else {
            if (elect_one()) ring_item(dst, &maps.q32, colv, rowv, sb + BAR_RF1 + 8 * id, 10240);
            rowv += 64;
          }
          mask >>= 1; xmask >>= 1;
          pm ^= 1u << id;
          id = id == 7 ? (i < 8 ? 0 : 3) : id + 1;
        }
      }
      {
        const uint32_t dst0 = sb + RING_OFF + (USE_MC ? rank * 6144 : 0);
        uint32_t so = 8 * POS_K, pm = ~PH_ALL;
#pragma unroll 1
        for (int sec = 0; sec < 3; sec++) {
          const CUtensorMap* m0 = sec == 1 ? &maps.w1_32 : &maps.q32;
          const int col = sec == 1 ? 1024 + 88 * c : (sec == 0 ? 640 : 0) + 80 * c;
          const uint32_t fb = sb + (sec == 1 ? BAR_RF : BAR_RF1) + 24, bytes = sec == 1 ? 11264 : 10240;
#pragma unroll 1
          for (int row = USE_MC ? rank * 32 : 0; row < 640; row += 64) {
            const uint32_t dst = dst0 + so * (SLOT / 8);
            mbar_wait(sb + BAR_RE + 24 + so, (pm >> so) & 1);
            STAMP2_IF(lane == 0, 64 + 24 + sec * 10 + (row >> 6));
            if (elect_one()) ring_item(dst, m0, col, row, fb + so, bytes);
            pm ^= 1u << so; so = (so + 8) & 24;
            if (sec == 0 && (row >> 6) == 4) {
              mbar_wait(sb + BAR_GOK, 0); mbar_wait(sb + BAR_RE + 8 * 7, 0);
              fence_async_global();
              if (elect_one()) { mbar_expect_tx(sb + BAR_WPHI, 12800); bulk_g2s(sb + WPHI_OFF, g_wphi + c * 800, 12800, sb + BAR_WPHI); }
            }
          }
        }
      }
      bar_sync(14, 160);
      fence_async_smem();
      if (lane < 4) mbar_arrive_cluster(sb + BAR_X + 8 * 10, lane & 1);
      __syncwarp();
    } else if (warp < 11) {
      unsigned tag;
      {
        const int g = lane >> 2, t = lane & 3;
        const int row = r * 128 + c * 16 + (warp - 9) * 8 + g;
        const __nv_bfloat16* xp = x + (size_t)row * kD + 8 * t;
        {
          const int kk = warp - 9;
          prefetch_l2(lane < 16 ? x + (size_t)(r * 128 + c * 16 + lane) * kD + kk * 64
                    : lane < 24 ? w1 + (size_t)((bid >> 1) + kk * 64) * kF + (bid & 1) * 512 + (lane - 16) * 64
                                : wqkv + (size_t)((bid >> 1) + kk * 64) * 1920 + 1280 + (bid & 1) * 320 + min(lane - 24, 4) * 64);
        }
        STAMP_IF(lane == 0 && warp == 9, 60);
        asm volatile("ld.relaxed.gpu.global.u32 %0, [%1];" : "=r"(tag) : "l"(g_pro) : "memory");
        CLUSTER_WAIT();
        while ((uint32_t)clock() - clk0 < J1_DELAY) {}
        tag = (tag >> 8) + 1;
        bar_arrive(6 + (tag & (gridDim.y - 1)), 96);
        float x0 = 0.f, s0 = 0.f, s1 = 0.f, q0 = 0.f, q1 = 0.f;
#pragma unroll 1
        for (int b = 0; b < 2; b++) {
          uint4 v[10];
#pragma unroll
          for (int i = 0; i < 10; i++) v[i] = ldg_nc128(xp + i * 32);
          xp += 320;
          if (b == 0) x0 = __shfl_sync(0xffffffffu, bf_lo(v[0].x), lane & ~3);
#pragma unroll
          for (int i = 0; i < 10; i++) {
            const uint32_t u[4] = {v[i].x, v[i].y, v[i].z, v[i].w};
#pragma unroll
            for (int e = 0; e < 4; e++) {
              const float d0 = bf_lo(u[e]) - x0, d1 = bf_hi(u[e]) - x0;
              s0 += d0; s1 += d1; q0 = fmaf(d0, d0, q0); q1 = fmaf(d1, d1, q1);
            }
          }
        }
        s0 += s1; q0 += q1;
        s0 += __shfl_xor_sync(0xffffffffu, s0, 1); q0 += __shfl_xor_sync(0xffffffffu, q0, 1);
        s0 += __shfl_xor_sync(0xffffffffu, s0, 2); q0 += __shfl_xor_sync(0xffffffffu, q0, 2);
        const float md = s0 * (1.f / kD);
        if (t == 0) st_relaxed128(g_stats + row, __float_as_uint(x0 + md), __float_as_uint(rsqrtf(fmaxf(fmaf(-md, md, q0 * (1.f / kD)), 0.f) + 1e-5f)), tag, tag);
        STAMP_IF(lane == 0 && warp == 9, 0);
      }
      if (warp == 9) {
        {
          uint4 v[4];
#pragma unroll 1
          for (int tries = 0; tries < (1 << 16); tries++) {
#pragma unroll
            for (int i = 0; i < 4; i++) v[i] = ld_relaxed128(g_stats + r * 128 + i * 32 + lane);
            if (v[0].z == tag && v[1].z == tag && v[2].z == tag && v[3].z == tag) break;
          }
#pragma unroll
          for (int i = 0; i < 4; i++) sts64f(sb + ST_OFF + (i * 32 + lane) * 8, __uint_as_float(v[i].x), __uint_as_float(v[i].y));
          bar_arrive(3, 64);
          STAMP_IF(lane == 0, 1);
        }
        mbar_wait(sb + BAR_GOK, 0);
        const char* hsrc = (const char*)g_h + (size_t)r * 216 * 2048;
        const char* osrc = (const char*)g_o + (size_t)r * 80 * 2048;
        uint32_t oready = 0;
#pragma unroll 1
        for (int q = 0; q < 22; q++) {
          if (q == 14 + c) { mbar_wait(sb + BAR_BE + 8 * (q & 3), ((q >> 2) - 1) & 1); continue; }
          const int b = q & 3;
          if (q == 0 || q == 8) {
            poll_ge(q == 0 ? &g_ha[(r * 2 + kap) * 32] : &g_hb[(r * 2 + kap) * 32], 4);
            fence_async_global();
            STAMP_IF(lane == 0, q == 0 ? 40 : 41);
          }
          if (q >= 14 && !((oready >> (q - 14)) & 1)) {
            const unsigned* fp = &g_oc[(r * 8 + (lane & 7)) * 32];
#pragma unroll 1
            for (int tries = 0; tries < (1 << 18); tries++) {
              unsigned v; asm volatile("ld.relaxed.gpu.global.u32 %0, [%1];" : "=r"(v) : "l"(fp) : "memory");
              oready = __ballot_sync(0xffffffffu, v != 0);
              if ((oready >> (q - 14)) & 1) break;
            }
            asm volatile("fence.acquire.gpu;" ::: "memory");
            fence_async_global();
            STAMP_IF(lane == 0 && q == 14 + (c == 0), 42);
          }
          if (q == KV_BUF0) mbar_wait(sb + BAR_X + 8 * 10, 0);
          mbar_wait(sb + (q < 4 ? BAR_X + 8 * ((XG_A >> (4 * q)) & 15) : BAR_BE + 8 * b), q < 4 ? 1 : ((q >> 2) - 1) & 1);
          if (MAXOUT && q >= MAXOUT) { const int p = q - MAXOUT; mbar_wait(sb + (p < 14 ? BAR_BF : BAR_BF1) + 8 * (p & 3), ((p < 14 ? p : p - 14) >> 2) & 1); }
          STAMP2_IF(lane == 0, 216 + q);
          const char* src = q < 8 ? hsrc + (64 * kap + 8 * q) * 2048 : q < 14 ? hsrc + (64 + 44 * kap + 8 * q) * 2048 : osrc + (q - 14) * 20480;
          const uint32_t bytes = q < 13 ? 16384 : q == 13 ? 8192 : 20480;
          if (elect_one()) {
            const uint32_t bar = sb + (q < 14 ? BAR_BF : BAR_BF1) + 8 * b;
            mbar_expect_tx(bar, bytes);
            bulk_g2s(sb + b * BUF_BYTES, src, bytes, bar);
          }
          __syncwarp();
        }
      } else {
        mbar_wait(sb + BAR_X + 8 * 2, 0); mbar_wait(sb + BAR_X + 8 * 4, 0); mbar_wait(sb + BAR_X + 8 * 5, 0);
        if (elect_one()) {
          if (PF2_ST < 0) {
            asm volatile("cp.async.bulk.prefetch.L2.global [%0], %1;" ::"l"((const char*)w2 + (size_t)bid * 17280), "r"(17280) : "memory");
            asm volatile("cp.async.bulk.prefetch.L2.global [%0], %1;" ::"l"((const char*)wo + (size_t)bid * 6400), "r"(6400) : "memory");
          }
          prefetch_map(&maps.w1_32); prefetch_map(&maps.w1_24);
          prefetch_map(&maps.w2_64); prefetch_map(&maps.w2_32); prefetch_map(&maps.wo_64); prefetch_map(&maps.wo_16); prefetch_map(&maps.y); prefetch_map(&maps.xr);
        }
        __syncwarp();
#pragma unroll 1
        for (int st = 0; st < 4; st++) {
          fetch_cs(sb, c, lane, tag, st == 0 ? 0 : st == 1 ? 64 : st == 2 ? 104 : 148, st == 0 ? 64 : st == 1 ? 104 : st == 2 ? 148 : 188);
          if (st == 0) { bar_sync(3, 64); mbar_wait(sb + BAR_X + 8 * 7, 0); mbar_wait(sb + BAR_X + 8 * 9, 0); }
          __syncwarp();
          if (lane == 0) mbar_arrive(sb + (st == 0 ? BAR_PRO : BAR_CS + 8 * st));
          STAMP_IF(lane == 0, 50 + st);
          if (st == PF2_ST) {
            for (int i = lane; i < 135; i += 32) prefetch_l2((const char*)w2 + (size_t)bid * 17280 + i * 128);
            for (int i = lane; i < 50; i += 32) prefetch_l2((const char*)wo + (size_t)bid * 6400 + i * 128);
          }
        }
#pragma unroll 1
        for (int q = 0; q < 22; q++) {
          const int b = q & 3;
          if (q == KV_BUF0) mbar_wait(sb + BAR_X + 8 * 10, 0);
          mbar_wait(sb + (q < 4 ? BAR_X + 8 * ((XG_B >> (4 * q)) & 15) : BAR_BE + 8 * b), q < 4 ? 1 : ((q >> 2) - 1) & 1);
          if (MAXOUT && q >= MAXOUT && q < 14 + MAXOUT) { const int p = q - MAXOUT; mbar_wait(sb + (p < 14 ? BAR_BF : BAR_BF1) + 8 * (p & 3), ((p < 14 ? p : p - 14) >> 2) & 1); }
          const uint32_t bar = sb + (q < 14 ? BAR_BF : BAR_BF1) + 8 * b;
          if (elect_one()) {
            if (q < 14) {
              const int k0 = q < 8 ? 512 * kap + 64 * q : 512 + 352 * kap + 64 * q;
              const uint32_t dst = sb + b * BUF_BYTES + 16384;
              mbar_expect_tx(bar, q < 13 ? 20480 : 10240);
              if (q < 13 || rank == 0)
              {
                tma_pair(dst, &maps.w2_64, 160 * jn, k0, 32, bar, rank);
                tma_pair(dst + 8192, &maps.w2_64, 160 * jn + 64, k0, 32, bar, rank);
                tma_pair(dst + 16384, &maps.w2_32, 160 * jn + 128, k0, 32, bar, rank);
              }
            } else {
              const int k0 = (q - 14) * 80;
              const int n0 = 160 * jn + 80 * kap;
              const uint32_t dst = sb + b * BUF_BYTES + 20480;
              mbar_expect_tx(bar, 12800);
              if (q == 14 + c) mbar_arrive(bar);
              tma_pair(dst, &maps.wo_64, n0, k0, 40, bar, rank);
              tma_pair(dst + 10240, &maps.wo_16, n0 + 64, k0, 40, bar, rank);
            }
          }
          __syncwarp();
        }
      }
    } else {
      if (elect_one()) { prefetch_map(&maps.w1a); prefetch_map(&maps.q32); prefetch_map(&maps.q16); }
      STAMP_IF(lane == 0, 59);
      if (lane < 25) {
        const int e = r * 50 + 2 * lane;
        const int k = e / 10, j = e - k * 10, h = k / 20;
        const uint2 wv = *(const uint2*)(wphi + c * 1600 + e * 2);
        uint4* dst = g_wphi + c * 800 + j * 8 + (k >> 3) * 80 + (k & 7);
        dst[0] = make_uint4(h == 0 ? wv.x : 0u, h == 1 ? wv.x : 0u, h == 2 ? wv.x : 0u, h == 3 ? wv.x : 0u);
        dst[8] = make_uint4(h == 0 ? wv.y : 0u, h == 1 ? wv.y : 0u, h == 2 ? wv.y : 0u, h == 3 ? wv.y : 0u);
      }
      for (int i = lane; i < 80; i += 32) g_kv[bid * 80 + i] = make_float4(0.f, 0.f, 0.f, 0.f);
#pragma unroll 1
      for (int i = 0; i < NPOISON; i++) g_part[(size_t)bid * 1280 + i * 32 + lane] = make_uint4(~0u, ~0u, ~0u, ~0u);
      if (lane == 0) g_oc[bid * 32] = 0;
      if (lane == 1 && bid < 32) g_ha[bid * 32] = 0;
      if (lane == 2 && bid < 32) g_hb[bid * 32] = 0;
      CLUSTER_WAIT();
      bar_sync(6, 96);
      unsigned old = 0;
      if (lane == 0) {
        asm volatile("atom.release.gpu.global.add.u32 %0, [%1], 1;" : "=r"(old) : "l"(g_pro) : "memory");
        STAMP(43);
        poll_ge(g_pro, (old & ~255u) + 256u);
        STAMP(44);
        mbar_arrive(sb + BAR_GOK);
      }
      const unsigned tag = (__shfl_sync(0xffffffffu, old, 0) >> 8) + 1;
#pragma unroll 1
      for (int e = 0; e < 2; e++) {
        bar_sync(7 + e, 160);
        if (lane == 0) { red_release(e == 0 ? &g_ha[(r * 2 + kap) * 32] : &g_hb[(r * 2 + kap) * 32]); STAMP(45 + e); }
        __syncwarp();
      }
      fetch_cs(sb, c, lane, tag, 188, 228);
    }
    if (warp == 8 || warp == 11) {
      build_kvb(sb, c, warp & 1, lane);
      STAMP_IF(lane == 0 && warp == 8, 35);
      if (warp == 11) {
        bar_sync(10, 160);
        if (lane == 0) {
          red_release(&g_oc[(r * 8 + c) * 32]);
          STAMP(48);
        }
      } else {
        bar_sync(9, 160);
        if (elect_one()) {
          mbar_expect_tx(sb + BAR_XR, 20480);
          tma2d(sb + Y_OFF, &maps.xr, 160 * jn + 80 * kap, r * 128, sb + BAR_XR);
        }
      }
      __syncwarp();
    }
    CLUSTER_ARRIVE(); CLUSTER_WAIT();
  } else if (warp < 4) {
    asm volatile("setmaxnreg.inc.sync.aligned.u32 200;");
    const int tid = threadIdx.x, w = warp;
    uint32_t ph = 0;
    const Rel rel(sb, tid);
    const uint32_t zero = gridDim.y - 1;
    uint32_t ha[64];
    uint4* const pown = g_part + (size_t)bid * 1280 + tid;
    CLUSTER_WAIT();
    char* hp = (char*)g_h + (size_t)r * 216 * 2048 + w * 256 + lane * 4;
    {
      float a0[64], a1[64];
      uint32_t prev = BAR_DUMMY;
#pragma unroll 1
      for (int j = 0; j < 13; j++) {
        const uint32_t id = (uint32_t)(P1_SLOT_A >> (4 * j)) & 7;
        const uint64_t db = mkdesc(sb + RING0, 6144, 1024, 1) + id * (SLOT / 16);
        const uint64_t dx = mkdesc(sb, 16, 1024, 1);
        const int k16 = 3 * j;
        const uint64_t da0 = dx + (k16 >> 2) * 1024 + (k16 & 3) * 2, da1 = dx + ((k16 + 1) >> 2) * 1024 + ((k16 + 1) & 3) * 2, da2 = dx + ((k16 + 2) >> 2) * 1024 + ((k16 + 2) & 3) * 2;
        mbar_wait(sb + BAR_X + 8 * ((k16 + 2) >> 2), 0);
        mbar_wait(sb + BAR_RF + 8 * id, (ph >> id) & 1);
        STAMP2_IF(tid == 0, 128 + j);
        wg_fence();
        wgmma_ss(a0, da0, db, j); wgmma_ss(a1, da0 + 512, db, j);
        wg_commit();
        wg_wait<1>();
        rel(prev);
        wgmma_ss(a0, da1, db + 128, 1); wgmma_ss(a1, da1 + 512, db + 128, 1);
        wgmma_ss(a0, da2, db + 256, 1); wgmma_ss(a1, da2 + 512, db + 256, 1);
        wg_commit();
        ph ^= 1u << id; prev = BAR_RE + 8 * id;
      }
      {
        constexpr uint32_t id = (uint32_t)(P1_SLOT_A >> 52) & 7;
        mbar_wait(sb + BAR_RF + 8 * id, (ph >> id) & 1);
        const uint64_t db = mkdesc(sb + RING0 + id * SLOT + 4096, 6144, 1024, 1), da = mkdesc(sb + 9 * 16384 + 96, 16, 1024, 1);
        wg_fence();
        wgmma_ss(a0, da, db, 1); wgmma_ss(a1, da + 512, db, 1);
        wg_commit();
        wg_wait<0>();
        rel(prev); rel(BAR_RE + 8 * id);
      }
      ph = PH_A;
      reg_fence(a0); reg_fence(a1);
      STAMP_IF(tid == 0, 2);
      mbar_wait(sb + BAR_PRO, 0);
      epi_h(a0, a1, ha, sb, CS_W1A, w, lane, zero);
      STAMP_IF(tid == 0, 3);
    }
    {
      float a0[44], a1[44];
      uint32_t so = 8 * POS_W1B;
      bar_sync(15, 256);
      store_h<64, 0, HA_SPLIT>(ha, hp + (size_t)(16 * c) * 2048);
      bar_sync(13, 256);
#pragma unroll 1
      for (int part = 0; part < 2; part++) {
        const int k0 = part ? NPRE1 : 0, k1 = part ? 10 : NPRE1;
        uint32_t prev_r = BAR_DUMMY, prev_x = BAR_DUMMY;
        tile_loop(a0, a1, sb, BAR_RF, ph, so, k0, k1, rel, prev_r, prev_x, 8, -1, 128 + 34, clk0);
        wg_wait<0>();
        rel(prev_r); rel(prev_x);
        if (part == 0) {
          bar_arrive(11, 256);
          store_h<64, HA_SPLIT, 64>(ha, hp + (size_t)(16 * c) * 2048);
          bar_arrive(7, 160);
          STAMP_IF(tid == 0, 4);
          bar_sync(12, 256);
        }
      }
      reg_fence(a0); reg_fence(a1);
      STAMP_IF(tid == 0, 5);
      uint32_t hb[44];
      mbar_wait(sb + BAR_CS + 16, 0);
      epi_h(a0, a1, hb, sb, CS_W1B, w, lane, zero);
      STAMP_IF(tid == 0, 6);
      bar_sync(15, 256);
      store_h<44, 0, 44>(hb, hp + (size_t)(128 + 11 * c) * 2048);
      bar_arrive(8, 160);
      STAMP_IF(tid == 0, 7);
    }
    {
      float a0[80], a1[80];
      bar_sync(13, 256);
#pragma unroll 1
      for (int q = 0; q < 13; q++) {
        const int b = q & 3;
        mbar_wait(sb + BAR_BF + 8 * b, (q >> 2) & 1);
        STAMP2_IF(tid == 0, 192 + q);
        uint64_t da = mkdesc(sb + b * BUF_BYTES, 2048, 128, 0);
        uint64_t db = mkdesc(sb + b * BUF_BYTES + 16384, 8192, 1024, 1);
        wg_fence();
        wgmma_ss(a0, da, db, q); wgmma_ss(a1, da + 64, db, q);
        wg_commit();
        wg_wait<1>();
        if (q > 0 && q != NPRE2 && q != QPAUSE + 1) rel(BAR_BE + 8 * ((q - 1) & 3));
#pragma unroll
        for (int kk = 1; kk < 4; kk++) { wgmma_ss(a0, da + kk * 256, db + kk * 128, 1); wgmma_ss(a1, da + kk * 256 + 64, db + kk * 128, 1); }
        wg_commit();
        if (q == NPRE2 - 1 || q == QPAUSE) {
          wg_wait<0>();
          rel(BAR_BE + 8 * b);
          STAMP_IF(tid == 0 && q == QPAUSE, 14);
          bar_sync(11, 256); bar_sync(12, 256);
        }
      }
      {
        mbar_wait(sb + BAR_BF + 8 * 1, 1);
        uint64_t da = mkdesc(sb + 1 * BUF_BYTES, 2048, 128, 0);
        uint64_t db = mkdesc(sb + 1 * BUF_BYTES + 16384, 8192, 1024, 1);
        wg_fence();
#pragma unroll
        for (int kk = 0; kk < 2; kk++) { wgmma_ss(a0, da + kk * 256, db + kk * 128, 1); wgmma_ss(a1, da + kk * 256 + 64, db + kk * 128, 1); }
        wg_commit();
        wg_wait<1>();
        rel(BAR_BE + 8 * 0);
      }
      wg_wait<0>();
      rel(BAR_BE + 8 * (13 & 3));
      reg_fence(a0); reg_fence(a1);
      STAMP_IF(tid == 0, 8);
      const int partner = bid ^ 64;
      uint4* pd = g_part + (size_t)partner * 1280 + tid;
      if (kap) {
#pragma unroll
        for (int i = 0; i < 5; i++) {
          st_relaxed128(pd + i * 128, pack_bf16(a0[8 * i], a0[8 * i + 1]), pack_bf16(a0[8 * i + 2], a0[8 * i + 3]), pack_bf16(a0[8 * i + 4], a0[8 * i + 5]), pack_bf16(a0[8 * i + 6], a0[8 * i + 7]));
          st_relaxed128(pd + (5 + i) * 128, pack_bf16(a1[8 * i], a1[8 * i + 1]), pack_bf16(a1[8 * i + 2], a1[8 * i + 3]), pack_bf16(a1[8 * i + 4], a1[8 * i + 5]), pack_bf16(a1[8 * i + 6], a1[8 * i + 7]));
        }
#pragma unroll
        for (int i = 0; i < 40; i++) { a0[i] = 0.5f * a0[40 + i]; a1[i] = 0.5f * a1[40 + i]; }
      } else {
#pragma unroll
        for (int i = 5; i < 10; i++) {
          st_relaxed128(pd + (i - 5) * 128, pack_bf16(a0[8 * i], a0[8 * i + 1]), pack_bf16(a0[8 * i + 2], a0[8 * i + 3]), pack_bf16(a0[8 * i + 4], a0[8 * i + 5]), pack_bf16(a0[8 * i + 6], a0[8 * i + 7]));
          st_relaxed128(pd + i * 128, pack_bf16(a1[8 * i], a1[8 * i + 1]), pack_bf16(a1[8 * i + 2], a1[8 * i + 3]), pack_bf16(a1[8 * i + 4], a1[8 * i + 5]), pack_bf16(a1[8 * i + 6], a1[8 * i + 7]));
        }
#pragma unroll
        for (int i = 0; i < 40; i++) { a0[i] *= 0.5f; a1[i] *= 0.5f; }
      }
      STAMP_IF(tid == 0, 9);
      bar_sync(4, 256);
      uint4 pv[10];
#pragma unroll 1
      for (int tries = 0; tries < (1 << 16); tries++) {
        uint32_t mx = 0;
#pragma unroll
        for (int i = 0; i < 10; i++) pv[i] = ld_relaxed128(pown + i * 128);
#pragma unroll
        for (int i = 0; i < 10; i++) mx = max(max(mx, max(pv[i].x, pv[i].y)), max(pv[i].z, pv[i].w));
        if (mx != ~0u) break;
      }
      STAMP_IF(tid == 0, 10);
#pragma unroll
      for (int i = 0; i < 10; i++) {
        const uint32_t pp[4] = {pv[i].x, pv[i].y, pv[i].z, pv[i].w};
        uint32_t o[4];
#pragma unroll
        for (int u = 0; u < 4; u++) {
          const float s0 = i < 5 ? a0[8 * i + 2 * u] : a1[8 * (i - 5) + 2 * u], s1 = i < 5 ? a0[8 * i + 2 * u + 1] : a1[8 * (i - 5) + 2 * u + 1];
          o[u] = pack_bf16(silu_half(fmaf(bf_lo(pp[u]), 0.5f, s0)), silu_half(fmaf(bf_hi(pp[u]), 0.5f, s1)));
        }
        sts128(sb + G_OFF + (i * 128 + tid) * 16, o[0], o[1], o[2], o[3]);
      }
      bar_arrive(5, 256);
      STAMP_IF(tid == 0, 11);
    }
    CLUSTER_ARRIVE(); CLUSTER_WAIT();
  } else {
    asm volatile("setmaxnreg.inc.sync.aligned.u32 240;");
    const int tid = threadIdx.x - 128, w = warp - 4;
    const int g = lane >> 2, t = lane & 3;
    uint32_t ph = 0;
    const Rel rel(sb, tid);
    uint32_t vf0[20], vf1[20];
    {
      CLUSTER_WAIT();
      float a0[40], a1[40];
#pragma unroll 1
      for (int k = 0; k < 10; k++) {
        const uint32_t id = (uint32_t)(P1_SLOT_V >> (4 * k)) & 7;
        const uint64_t da = mkdesc(sb, 16, 1024, 1) + k * 1024, db = mkdesc(sb + RING0, 2048, 512, 2) + id * (SLOT / 16);
        mbar_wait(sb + BAR_X + 8 * k, 0); mbar_wait(sb + BAR_RF1 + 8 * id, (ph >> id) & 1);
        STAMP2_IF(tid == 0, 142 + k);
        wg_fence();
        wgmma_ss(a0, da, db, k); wgmma_ss(a1, da + 512, db, k); wgmma_ss(a0, da + 2, db + 64, 1); wgmma_ss(a1, da + 514, db + 64, 1);
        wgmma_ss(a0, da + 4, db + 384, 1); wgmma_ss(a1, da + 516, db + 384, 1); wgmma_ss(a0, da + 6, db + 448, 1); wgmma_ss(a1, da + 518, db + 448, 1);
        wg_commit();
        ph ^= 1u << id;
        wg_wait<0>();
        rel(BAR_RE + 8 * id);
      }
      ph = PH_V;
      reg_fence(a0); reg_fence(a1);
      STAMP_IF(tid == 0, 18);
      mbar_wait(sb + BAR_PRO, 0);
      RowStats st; load_stats(st, sb, w, g);
#pragma unroll
      for (int j = 0; j < 20; j++) {
        vf0[j] = pack_bf16(a0[2 * j] * st.rstd[0][j & 1], a0[2 * j + 1] * st.rstd[0][j & 1]);
        vf1[j] = pack_bf16(a1[2 * j] * st.rstd[1][j & 1], a1[2 * j + 1] * st.rstd[1][j & 1]);
      }
      STAMP_IF(tid == 0, 19);
    }
    float4* kp = g_kv + (c * 4 + w) * 320 + lane;
    asm volatile("" : "+l"(kp));
    uint32_t o00[20], o01[20], o10[20], o11[20];
#pragma unroll 1
    for (int it = 0; it < 2; it++) {
      float a0[40], a1[40];
      uint32_t so = 8 * POS_K, prev_r = BAR_DUMMY, prev_x = BAR_DUMMY;
#pragma unroll
      for (int part = 0; part < 2; part++) {
        tile_loop(a0, a1, sb, BAR_RF1, ph, so, part ? KSPLIT : 0, part ? 10 : KSPLIT, rel, prev_r, prev_x, it * 8, it ? KSIG_Q : KSIG_K, 128 + 24 + 20 * it, clk0);
        if (part == 0 && it) {
          RowStats st; load_stats(st, sb, w, g);
          const uint32_t va = sb + V_OFF + (16 * w + (lane & 15)) * V_PITCH + (lane >> 4) * 16;
          uint32_t e[2][2];
#pragma unroll
          for (int m = 0; m < 2; m++)
#pragma unroll
            for (int i = 0; i < 2; i++) e[m][i] = (t & 1) ? 0u : pack_bf16(1.f, st.mean[m][i] * st.rstd[m][i]);
          STAMP_IF(tid == 0, 21);
          bar_sync(2, 128);
#pragma unroll
          for (int m = 0; m < 2; m++) {
            const uint32_t (&vf)[20] = m ? vf1 : vf0;
            const uint32_t vb = va + m * 64 * V_PITCH;
#pragma unroll
            for (int p = 0; p < 2; p++) {
              const int j = 10 * p;
              stsm4(vb + p * 96, vf[j], vf[j + 1], vf[j + 2], vf[j + 3]);
              stsm4(vb + p * 96 + 32, t < 2 ? vf[j + 4] : e[m][0], t < 2 ? vf[j + 5] : e[m][1], t < 2 ? e[m][0] : vf[j + 4], t < 2 ? e[m][1] : vf[j + 5]);
              stsm4(vb + p * 96 + 64, vf[j + 6], vf[j + 7], vf[j + 8], vf[j + 9]);
            }
          }
          const uint32_t pk = sb + PHIK_OFF + t * PHI_HS + (16 * w + g) * 80;
          store_phi(pk, o00); store_phi(pk + 640, o01); store_phi(pk + PHI_HALF, o10); store_phi(pk + PHI_HALF + 640, o11);
          uint32_t av = sb + V_OFF + ((lane >> 4) * 8 + (lane & 7)) * V_PITCH + w * 48 + ((lane >> 3) & 1) * 16;
          uint32_t av2 = sb + V_OFF + (lane & 15) * V_PITCH + w * 48 + 32;
          uint32_t bp = sb + PHIK_OFF + w * PHI_HS + (lane & 15) * 80 + (lane >> 4) * 16;
          wg_wait<0>();
          rel(prev_r); rel(prev_x); prev_r = BAR_DUMMY; prev_x = BAR_DUMMY;
          float kv[2][5][4];
#pragma unroll
          for (int i = 0; i < 10; i++) { kv[i / 5][i % 5][0] = 0.f; kv[i / 5][i % 5][1] = 0.f; kv[i / 5][i % 5][2] = 0.f; kv[i / 5][i % 5][3] = 0.f; }
#pragma unroll 1
          for (int m = 0; m < 2; m++) {
            if (m == 0) { bar_sync(2, 128); STAMP_IF(tid == 0, 23); }
            uint32_t a[4][4], a2[4][2], b[4][10];
#pragma unroll
            for (int ks = 0; ks < 4; ks++) {
              ldsm4t(av + ks * 16 * V_PITCH, a[ks][0], a[ks][1], a[ks][2], a[ks][3]);
              ldsm4t(bp + ks * 1280, b[ks][0], b[ks][1], b[ks][2], b[ks][3]);
              ldsm2t(av2 + ks * 16 * V_PITCH, a2[ks][0], a2[ks][1]);
              ldsm4t(bp + ks * 1280 + 32, b[ks][4], b[ks][5], b[ks][6], b[ks][7]);
              ldsm2t(bp + ks * 1280 + 64, b[ks][8], b[ks][9]);
            }
#pragma unroll
            for (int ks = 0; ks < 4; ks++)
#pragma unroll
              for (int nf = 0; nf < 5; nf++) {
                mma16816(kv[0][nf], a[ks][0], a[ks][1], a[ks][2], a[ks][3], b[ks][2 * nf], b[ks][2 * nf + 1]);
                mma16816(kv[1][nf], a2[ks][0], 0u, a2[ks][1], 0u, b[ks][2 * nf], b[ks][2 * nf + 1]);
              }
            av += 64 * V_PITCH; av2 += 64 * V_PITCH; bp += PHI_HALF;
          }
          bar_arrive(14, 160);
#pragma unroll
          for (int nf = 0; nf < 5; nf++)
#pragma unroll
            for (int e2 = 0; e2 < 2; e2++)
              asm volatile("red.relaxed.gpu.global.add.v4.f32 [%0], {%1, %2, %3, %4};" ::"l"(kp + (2 * nf + e2) * 32), "f"(kv[0][nf][e2]), "f"(kv[0][nf][2 + e2]), "f"(kv[1][nf][e2]), "f"(1.f) : "memory");
          STAMP_IF(tid == 0, 24);
        }
      }
      bar_arrive(13, 256);
      RowStats st; load_stats(st, sb, w, g);
      mbar_wait(sb + BAR_CS + 8 + 16 * it, 0);
      if (!it) mbar_wait(sb + BAR_WPHI, 0);
      wg_wait<0>();
      rel(prev_r); rel(prev_x);
      reg_fence(a0); reg_fence(a1);
      STAMP_IF(tid == 0, it ? 22 : 20);
      uint32_t f0[20], f1[20];
      fix_pack(a0, a1, f0, f1, st, sb + CS_OFF + ((it ? CS_Q : CS_K) + 2 * t) * 4);
      bar_sync(11, 256);
      STAMP_IF(tid == 0, it ? 36 : 32);
      wg_fence();
      phi_gemm(a0, f0, sb);
      phi_gemm(a1, f1, sb);
      bar_arrive(12, 256);
      wg_wait<0>();
      reg_fence(a0); reg_fence(a1);
      dual_softmax(a0, 0, st.rstd[0][0] * kLog2e, o00);
      dual_softmax(a0, 1, st.rstd[0][1] * kLog2e, o01);
      dual_softmax(a1, 0, st.rstd[1][0] * kLog2e, o10);
      dual_softmax(a1, 1, st.rstd[1][1] * kLog2e, o11);
      STAMP_IF(tid == 0, it ? 25 : 33);
    }
    {
      float o0[48], o1[48];
      const uint64_t db = mkdesc(sb + KVB_OFF, 1536, 128, 0);
      char* og = (char*)g_o + ((size_t)r * 80 + 10 * c) * 2048 + w * 256 + lane * 4;
      const uint32_t os = sb + O_OFF + (lane >> 4) * 2048 + w * 256 + (lane & 15) * 16;
      mbar_wait(sb + BAR_X + 8 * 11, 0);
      STAMP_IF(tid == 0, 26);
      bar_sync(11, 256);
      STAMP_IF(tid == 0, 34);
      wg_fence();
#pragma unroll
      for (int kk = 0; kk < 10; kk++) {
        if (kk == 0) wgmma_rs0(o0, o00[0], o01[0], o00[1], o01[1], db);
        else wgmma_rs(o0, o00[2 * kk], o01[2 * kk], o00[2 * kk + 1], o01[2 * kk + 1], db + kk * 192, 1);
      }
      wg_commit();
#pragma unroll
      for (int kk = 0; kk < 10; kk++) {
        if (kk == 0) wgmma_rs0(o1, o10[0], o11[0], o10[1], o11[1], db);
        else wgmma_rs(o1, o10[2 * kk], o11[2 * kk], o10[2 * kk + 1], o11[2 * kk + 1], db + kk * 192, 1);
      }
      wg_commit();
      bar_arrive(12, 256);
      auto fin = [&](float (&o)[48], int m) {
        uint32_t pk[20];
#pragma unroll
        for (int i = 0; i < 2; i++) {
          const float r0 = rcp(o[40 + 2 * i] + 1e-6f), r1 = rcp(o[41 + 2 * i] + 1e-6f), r2 = rcp(o[44 + 2 * i] + 1e-6f), r3 = rcp(o[45 + 2 * i] + 1e-6f);
          const float rA = t < 2 ? r0 : r1, rB = t < 2 ? r2 : r3;
#pragma unroll
          for (int j = 0; j < 10; j++) {
            const float rr = j < 2 ? r0 : j == 2 ? rA : j < 5 ? r1 : j < 7 ? r2 : j == 7 ? rB : r3;
            pk[2 * j + i] = pack_bf16(o[4 * j + 2 * i] * rr, o[4 * j + 2 * i + 1] * rr);
            stg32(og + j * 2048 + m * 1024 + i * 128, pk[2 * j + i]);
          }
        }
#pragma unroll
        for (int j = 0; j < 5; j++) stsm4(os + j * 4096 + m * 1024, pk[4 * j], pk[4 * j + 1], pk[4 * j + 2], pk[4 * j + 3]);
      };
      wg_wait<1>(); reg_fence(o0);
      fin(o0, 0);
      wg_wait<0>(); reg_fence(o1);
      fin(o1, 1);
      bar_arrive(10, 160);
      fence_async_smem();
      bar_arrive(4, 256);
      bar_sync(9, 160);
      STAMP_IF(tid == 0, 27);
    }
    {
      const int n0 = 160 * jn + 80 * kap;
      float a0[40], a1[40];
#pragma unroll 1
      for (int q = 14; q < 22; q++) {
        const int b = q & 3;
        mbar_wait(sb + BAR_BF1 + 8 * b, ((q - 14) >> 2) & 1);
        STAMP2_IF(tid == 0, 192 + q);
        uint64_t da = mkdesc(sb + (q == 14 + c ? O_OFF : b * BUF_BYTES), 2048, 128, 0);
        uint64_t db = mkdesc(sb + b * BUF_BYTES + 20480, 10240, 1024, 1);
        wg_fence();
        wgmma_ss(a0, da, db, q - 14); wgmma_ss(a1, da + 64, db, q - 14);
        wg_commit();
        wg_wait<1>();
        if (q > 14 && q <= 18) rel(BAR_BE + 8 * ((q - 1) & 3));
#pragma unroll
        for (int kk = 1; kk < 5; kk++) { wgmma_ss(a0, da + kk * 256, db + kk * 128, 1); wgmma_ss(a1, da + kk * 256 + 64, db + kk * 128, 1); }
        wg_commit();
      }
      CLUSTER_ARRIVE();
      uint32_t xr[40];
      const uint32_t ya = sb + Y_OFF + (16 * w + (lane & 15)) * 160 + (lane >> 4) * 16;
      mbar_wait(sb + BAR_XR, 1);
#pragma unroll
      for (int i = 0; i < 10; i++) ldsm4(ya + (i / 5) * 10240 + (i % 5) * 32, xr[4 * i], xr[4 * i + 1], xr[4 * i + 2], xr[4 * i + 3]);
      bar_sync(5, 256);
      STAMP_IF(tid == 0, 30);
      uint4 gv[10];
#pragma unroll
      for (int i = 0; i < 10; i++) gv[i] = lds128(sb + G_OFF + (i * 128 + tid) * 16);
      wg_wait<0>();
      reg_fence(a0); reg_fence(a1);
      STAMP_IF(tid == 0, 29);
#pragma unroll
      for (int m = 0; m < 2; m++) {
#pragma unroll
        for (int i = 0; i < 5; i++) {
          const uint32_t gg[4] = {gv[m * 5 + i].x, gv[m * 5 + i].y, gv[m * 5 + i].z, gv[m * 5 + i].w};
          uint32_t y[4];
#pragma unroll
          for (int u = 0; u < 4; u++) {
            const float s0 = m ? a1[8 * i + 2 * u] : a0[8 * i + 2 * u], s1 = m ? a1[8 * i + 2 * u + 1] : a0[8 * i + 2 * u + 1];
            const uint32_t xv = xr[m * 20 + 4 * i + u];
            y[u] = pack_bf16(fmaf(s0, bf_lo(gg[u]), bf_lo(xv)), fmaf(s1, bf_hi(gg[u]), bf_hi(xv)));
          }
          stsm4(ya + m * 10240 + i * 32, y[0], y[1], y[2], y[3]);
        }
        fence_async_smem();
        __syncwarp();
        if (elect_one()) {
          asm volatile("cp.async.bulk.tensor.2d.global.shared::cta.tile.bulk_group [%0, {%2, %3}], [%1];" ::"l"(&maps.y), "r"(sb + Y_OFF + m * 10240 + w * 2560), "r"(n0), "r"(r * 128 + 64 * m + 16 * w) : "memory");
          asm volatile("cp.async.bulk.commit_group;" ::: "memory");
        }
      }
      asm volatile("cp.async.bulk.wait_group.read 0;" ::: "memory");
      __syncwarp();
      STAMP_IF(tid == 0, 31);
    }
    CLUSTER_WAIT();
  }
}

typedef CUresult (*EncodeFn)(CUtensorMap*, CUtensorMapDataType, cuuint32_t, void*, const cuuint64_t*, const cuuint64_t*, const cuuint32_t*,
                             const cuuint32_t*, CUtensorMapInterleave, CUtensorMapSwizzle, CUtensorMapL2promotion, CUtensorMapFloatOOBfill);

void make_map(EncodeFn fn, CUtensorMap* m, const void* ptr, uint64_t cols, uint64_t rows, uint32_t bc, uint32_t br, CUtensorMapSwizzle sw, uint32_t panels = 0) {
  cuuint64_t dims[3] = {cols, rows, panels};
  cuuint64_t strides[2] = {cols * 2, (cuuint64_t)bc * 2};
  cuuint32_t box[3] = {bc, br, panels}, es[3] = {1, 1, 1};
  CUresult res = fn(m, CU_TENSOR_MAP_DATA_TYPE_BFLOAT16, panels ? 3 : 2, const_cast<void*>(ptr), dims, strides, box, es, CU_TENSOR_MAP_INTERLEAVE_NONE,
     sw, CU_TENSOR_MAP_L2_PROMOTION_L2_128B, CU_TENSOR_MAP_FLOAT_OOB_FILL_NONE);
  (void)res;
}

}

extern "C" void kernel_launch(void* const* d_in, const int* in_sizes, int n_in, void* d_out, int out_size) {
  (void)in_sizes; (void)n_in; (void)out_size;
  const __nv_bfloat16* x = (const __nv_bfloat16*)d_in[0];
  const __nv_bfloat16* wqkv = (const __nv_bfloat16*)d_in[1];
  const __nv_bfloat16* wphi = (const __nv_bfloat16*)d_in[2];
  const __nv_bfloat16* wo = (const __nv_bfloat16*)d_in[3];
  const __nv_bfloat16* w1 = (const __nv_bfloat16*)d_in[5];
  const __nv_bfloat16* w2 = (const __nv_bfloat16*)d_in[6];
  void* fnp = nullptr;
  cudaDriverEntryPointQueryResult qr;
  cudaGetDriverEntryPoint("cuTensorMapEncodeTiled", &fnp, cudaEnableDefault, &qr);
  EncodeFn fn = (EncodeFn)fnp;
  Maps maps;
  const CUtensorMapSwizzle S128 = CU_TENSOR_MAP_SWIZZLE_128B, S64 = CU_TENSOR_MAP_SWIZZLE_64B;
  make_map(fn, &maps.x, x, 640, 2048, 64, 128, S128);
  make_map(fn, &maps.w1a, w1, 1728, 640, 64, 48, S128);
  make_map(fn, &maps.q32, wqkv, 1920, 640, 32, 32, S64, 2);
  make_map(fn, &maps.q16, wqkv, 1920, 640, 16, 32, S64);
  make_map(fn, &maps.jq, wqkv, 1920, 640, 64, 128, S128);
  make_map(fn, &maps.jw, w1, 1728, 640, 64, 128, S128);
  make_map(fn, &maps.w1_32, w1, 1728, 640, 32, 32, S64, 2);
  make_map(fn, &maps.w1_24, w1, 1728, 640, 24, 32, S64);
  make_map(fn, &maps.w2_64, w2, 640, 1728, 64, 32, S128);
  make_map(fn, &maps.w2_32, w2, 640, 1728, 32, 32, S128);
  make_map(fn, &maps.wo_64, wo, 640, 640, 64, 40, S128);
  make_map(fn, &maps.wo_16, wo, 640, 640, 16, 40, S128);
  make_map(fn, &maps.xr, x, 640, 2048, 80, 128, CU_TENSOR_MAP_SWIZZLE_NONE);
  make_map(fn, &maps.y, d_out, 640, 2048, 80, 16, CU_TENSOR_MAP_SWIZZLE_NONE);
  cudaFuncSetAttribute(fused_kernel, cudaFuncAttributeMaxDynamicSharedMemorySize, SMEM_BYTES);
  fused_kernel<<<132, 384, SMEM_BYTES, cudaStreamPerThread>>>(x, wqkv, wphi, w1, w2, wo, maps);
}
```

```cpp
#include <cuda_runtime.h>
#include <cuda.h>
#include <cuda_bf16.h>
#include <stdint.h>

#define USE_MC 1
#define NPRE1 1
#define PFLEAD 2
#define XG_A 0x8770
#define XG_B 0x9772
#define W1A_LAG 1
#define JB 10
#define PFW_X 0
#define J1_DELAY 0
#define J2_DELAY 0
#define JPOS 7
#define JA 3
#define JV 2
#define PFALL 0
#define E1_DIST 20
#define E1_TAP 1
#define NPRE2 1
#define KV_FIRST 1
#define LL_PRE 1
#define HB_X 7
#define EXTRA_FIRST 0
#define KSIG_K 8
#define KSIG_Q 7
#define HA_SPLIT 24
#define NPOISON 40
#define PF2_ST 1
#define SM_MODE 2
#define PACE_A 330
#define PACE_B 140
#define PGRP 4
#define HA_STEPS 8
#define PHI_REL 0
#define LEAN_A 1
#define W2SW 128
#define WOSW 128
#define W2_LBO 8192
#define W2_SBO 1024
#define W2_MODE 1
#define W2_HALF 256
#define W2_STEP 128
#define FSPLIT 1
#define LL_WAIT 0
#define XEARLY 1
#define XLEADN 0
#define KV_LL 0
#define EARLY_STS 0
#define ROT 0
#define PPOLL 0
#define KV_V4 0
#define B3_PIN 0
#define KV_WG 0
#define ST_SMEM 0
#define TOP_PF 0
#define ST_RESET 1
#define CS_IN 0
#define FAST0 1
#define XFIRST 0
#define CS_HELP 0
#define B2_SPLIT 0
#define B3_LONG 0
#define SEND_PIN 0
#define QPAUSE 6
#define WAVE2_DELAY 600
#define J2_K0 2
#define XLEAD 2
#define MAP_MODE 2

#define PAUSE_MASK ((NPRE2 ? 1u << (NPRE2 - 1) : 0u) | (B2_SPLIT ? 1u << NPRE2 : 0u) | 1u << QPAUSE)

namespace {

constexpr int kD = 640, kF = 1728;
constexpr float kLog2e = 1.4426950408889634f;

constexpr uint32_t RING_OFF = 163840, SLOT = 12288, WPHI_OFF = RING_OFF + 4 * SLOT, MISC_OFF = 229152, SMEM_BYTES = 232448;
constexpr uint32_t RING0 = RING_OFF - 3 * SLOT;
constexpr uint32_t BAR_X = MISC_OFF, BAR_PRO = BAR_X + 96, BAR_WPHI = BAR_PRO + 8, BAR_DUMMY = BAR_PRO + 16, BAR_GOK = BAR_PRO + 24, BAR_XR = BAR_PRO  , BAR_RF = BAR_X + 128, BAR_RF1 = BAR_RF + 64,
                   BAR_RE = BAR_RF1 + 64, BAR_BE = BAR_RE + 64, BAR_BF = BAR_BE + 32, BAR_BF1 = BAR_BF + 32, BAR_CS = BAR_BF1 + 32, BAR_KV = BAR_CS;
constexpr uint32_t TAG_OFF = MISC_OFF - 16;
constexpr uint32_t CS_OFF = 229600, ST_OFF = CS_OFF + 1824;
static_assert(BAR_CS + 32 <= CS_OFF && ST_OFF + 1024 <= SMEM_BYTES, "smem map");
constexpr int CS_W1A = 0, CS_K = 128, CS_W1B = 208, CS_Q = 296, CS_V = 376;
constexpr uint32_t BUF_BYTES = 40960;
constexpr uint32_t V_OFF = RING_OFF, PHI_OFF = RING_OFF + 22528, PHI_HALF = 20608, PHIK0_OFF = RING_OFF + 26624, PHIK1_OFF = 3 * BUF_BYTES + 16384;
constexpr uint32_t VS_OFF = 3 * BUF_BYTES + 16384, PHIK_OFF = RING_OFF, PHIK_GS = 2080;
constexpr uint32_t O_OFF = RING_OFF, G_OFF = PHI_OFF, Y_OFF = PHI_OFF + PHI_HALF;
static_assert(PHI_OFF + 2 * PHI_HALF <= MISC_OFF && Y_OFF % 128 == 0, "scratch");
constexpr uint32_t V_PITCH = 208, PHI_HS = 5152;
constexpr int NCTA_MC = USE_MC ? 2 : 1;

#define P1_ORDER "AVAVAVAAVAVAVAAVAVAVAVAA"
#define P1_SLOTS "012345670123456734567345"
constexpr uint32_t order_mask(const char* p, char ch) { uint32_t m = 0; for (int i = 0; p[i]; i++) if (p[i] == ch) m |= 1u << i; return m; }
constexpr uint64_t order_slots(char ch) { uint64_t m = 0; int n = 0; for (int i = 0; i < 24; i++) if (P1_ORDER[i] == ch) { m |= (uint64_t)(P1_SLOTS[i] - '0') << (4 * n); n++; } return m; }
constexpr uint32_t order_phase(char ch) { uint32_t m = 0; for (int i = 0; i < 24; i++) { int id = P1_SLOTS[i] - '0'; if ((ch == 0 || P1_ORDER[i] == ch) && id >= 3) m ^= 1u << (id - 3); } return m; }
constexpr uint32_t order_xmask() {
  uint32_t m = 0; int ja = 0, kv = 0, have = 0;
  for (int i = 0; i < 24; i++) { int need = P1_ORDER[i] == 'A' ? (ja < 13 ? (3 * ja + 2) >> 2 : 9) : kv; if (P1_ORDER[i] == 'A') ja++; else kv++; if (need > have) { m |= 1u << i; have++; if (need > have || (have >= 7 && i < 9 + have)) return 0; } }
  return m;
}
constexpr uint32_t P1_MASK = order_mask(P1_ORDER, 'A'), P1_XMASK = order_xmask();
static_assert(P1_XMASK != 0, "bad pass-1 order");
constexpr uint64_t P1_SLOT_A = order_slots('A'), P1_SLOT_V = order_slots('V');
constexpr uint32_t PH_A = order_phase('A'), PH_V = order_phase('V'), PH_ALL = order_phase(0);
constexpr int RF0_USES = (P1_ORDER[0] == 'A') + (P1_ORDER[8] == 'A');
constexpr int POS_K = 3;

struct Maps { CUtensorMap x, w1a, q32, q16, jq, jw, w1_32, w1_24, w2_64, w2_32, wo_64, wo_16, y, xr; };

__device__ uint4 g_h[16 * 216 * 128];
__device__ uint4 g_o[16 * 80 * 128];
__device__ uint4 g_part[128 * 10 * 128];
__device__ __align__(16) float2 g_kv[8 * 4 * 15 * 32];
__device__ uint4 g_stats[2048];
__device__ uint4 g_colsum[8 * 228];
__device__ uint4 g_wphi[8 * 800];
__device__ unsigned g_pro[32];
__device__ unsigned g_ha[32 * 32], g_hb[32 * 32], g_kvc[8 * 32], g_oc[128 * 32];
#define STAMP2_IF(c, id)
#define STAMP(id)
#define STAMP_IF(c, id)
#define ERRFLAG
__device__ __forceinline__ uint32_t smem_u32(const void* p) { return (uint32_t)__cvta_generic_to_shared(p); }
__device__ __forceinline__ void mbar_init(uint32_t bar, uint32_t cnt) { asm volatile("mbarrier.init.shared::cta.b64 [%0], %1;" ::"r"(bar), "r"(cnt)); }
__device__ __forceinline__ void mbar_expect_tx(uint32_t bar, uint32_t bytes) { asm volatile("mbarrier.arrive.expect_tx.shared::cta.b64 _, [%0], %1;" ::"r"(bar), "r"(bytes) : "memory"); }
__device__ __forceinline__ void mbar_arrive(uint32_t bar) { asm volatile("mbarrier.arrive.shared::cta.b64 _, [%0];" ::"r"(bar) : "memory"); }
__device__ __forceinline__ void mbar_arrive_n(uint32_t bar, uint32_t n) { asm volatile("mbarrier.arrive.shared::cta.b64 _, [%0], %1;" ::"r"(bar), "r"(n) : "memory"); }
__device__ __forceinline__ void mbar_arrive_cluster(uint32_t bar, uint32_t cta) {
  asm volatile("{\n.reg .b32 ra;\nmapa.shared::cluster.u32 ra, %0, %1;\nmbarrier.arrive.shared::cluster.b64 _, [ra];\n}" ::"r"(bar), "r"(cta) : "memory");
}
__device__ __forceinline__ void mbar_wait(uint32_t bar, uint32_t parity) {
  asm volatile("{\n.reg .pred p;\n.reg .u32 c;\nmov.u32 c, 0;\nWL:\nmbarrier.try_wait.parity.shared::cta.b64 p, [%0], %1;\n@p bra WD;\nadd.u32 c, c, 1;\nsetp.lt.u32 p, c, 262144;\n@p bra WL;\nWD:\n}" ::"r"(bar), "r"(parity) : "memory");
}
__device__ __forceinline__ bool elect_one() {
  uint32_t p;
  asm volatile("{\n.reg .pred P;\nelect.sync _|P, 0xffffffff;\nselp.u32 %0, 1, 0, P;\n}" : "=r"(p));
  return p;
}
__device__ __forceinline__ void tma2d(uint32_t dst, const CUtensorMap* m, int c0, int c1, uint32_t bar) {
  asm volatile("cp.async.bulk.tensor.2d.shared::cluster.global.mbarrier::complete_tx::bytes [%0], [%1, {%3, %4}], [%2];" ::"r"(dst), "l"(m), "r"(bar), "r"(c0), "r"(c1) : "memory");
}
__device__ __forceinline__ void tma2d_mc(uint32_t dst, const CUtensorMap* m, int c0, int c1, uint32_t bar) {
  asm volatile("cp.async.bulk.tensor.2d.shared::cluster.global.mbarrier::complete_tx::bytes.multicast::cluster [%0], [%1, {%3, %4}], [%2], %5;" ::"r"(dst), "l"(m), "r"(bar), "r"(c0), "r"(c1), "h"((uint16_t)3) : "memory");
}
__device__ __forceinline__ void tma3d(uint32_t dst, const CUtensorMap* m, int c0, int c1, uint32_t bar) {
  asm volatile("cp.async.bulk.tensor.3d.shared::cluster.global.mbarrier::complete_tx::bytes [%0], [%1, {%3, %4, %5}], [%2];" ::"r"(dst), "l"(m), "r"(bar), "r"(c0), "r"(c1), "r"(0) : "memory");
}
__device__ __forceinline__ void tma3d_mc(uint32_t dst, const CUtensorMap* m, int c0, int c1, uint32_t bar) {
  asm volatile("cp.async.bulk.tensor.3d.shared::cluster.global.mbarrier::complete_tx::bytes.multicast::cluster [%0], [%1, {%3, %4, %5}], [%2], %6;" ::"r"(dst), "l"(m), "r"(bar), "r"(c0), "r"(c1), "r"(0), "h"((uint16_t)3) : "memory");
}
__device__ __forceinline__ void prefetch_l2(const void* p) { asm volatile("prefetch.global.L2 [%0];" ::"l"(p)); }
__device__ __forceinline__ void tma_pair(uint32_t dst, const CUtensorMap* m, int c0, int row0, int half_rows, uint32_t bar, uint32_t rank) {
  tma2d_mc(dst + rank * half_rows * 128, m, c0, row0 + rank * half_rows, bar);
}
__device__ __forceinline__ void bulk_g2s(uint32_t dst, const void* src, uint32_t bytes, uint32_t bar) {
  asm volatile("cp.async.bulk.shared::cluster.global.mbarrier::complete_tx::bytes [%0], [%1], %2, [%3];" ::"r"(dst), "l"(src), "r"(bytes), "r"(bar) : "memory");
}
__device__ __forceinline__ void prefetch_map(const CUtensorMap* m) { asm volatile("prefetch.tensormap [%0];" ::"l"(m) : "memory"); }
__device__ __forceinline__ void wg_fence() { asm volatile("wgmma.fence.sync.aligned;" ::: "memory"); }
__device__ __forceinline__ void wg_commit() { asm volatile("wgmma.commit_group.sync.aligned;" ::: "memory"); }
template <int N> __device__ __forceinline__ void wg_wait() { asm volatile("wgmma.wait_group.sync.aligned %0;" ::"n"(N) : "memory"); }
template <int R> __device__ __forceinline__ void reg_fence(float (&d)[R]) {
#pragma unroll
  for (int i = 0; i < R; i++) asm volatile("" : "+f"(d[i])::"memory");
}
__device__ __forceinline__ uint64_t mkdesc(uint32_t addr, uint32_t lbo, uint32_t sbo, uint32_t sw) {
  return (uint64_t)((addr & 0x3FFFF) >> 4) | ((uint64_t)(lbo >> 4) << 16) | ((uint64_t)(sbo >> 4) << 32) | ((uint64_t)sw << 62);
}
__device__ __forceinline__ void bar_sync(int id, int n) { asm volatile("bar.sync %0, %1;" ::"r"(id), "r"(n) : "memory"); }
__device__ __forceinline__ void bar_arrive(int id, int n) { asm volatile("bar.arrive %0, %1;" ::"r"(id), "r"(n) : "memory"); }
__device__ __forceinline__ void fence_gpu() { asm volatile("fence.acq_rel.gpu;" ::: "memory"); }
__device__ __forceinline__ void fence_async_smem() { asm volatile("fence.proxy.async.shared::cta;" ::: "memory"); }
__device__ __forceinline__ void fence_async_global() { asm volatile("fence.proxy.async.global;" ::: "memory"); }
__device__ __forceinline__ unsigned ld_acquire(const unsigned* p) { unsigned v; asm volatile("ld.acquire.gpu.global.u32 %0, [%1];" : "=r"(v) : "l"(p) : "memory"); return v; }
__device__ __forceinline__ void red_release(unsigned* p) { asm volatile("red.release.gpu.global.add.u32 [%0], 1;" ::"l"(p) : "memory"); }
__device__ __forceinline__ void poll_ge(const unsigned* p, unsigned target) {
  asm volatile("{\n.reg .pred p;\n.reg .u32 c, v;\nmov.u32 c, 0;\nPL:\nld.relaxed.gpu.global.u32 v, [%0];\nsub.u32 v, v, %1;\nsetp.ge.s32 p, v, 0;\n@p bra PD;\nadd.u32 c, c, 1;\nsetp.lt.u32 p, c, 262144;\n@p bra PL;\nPD:\nfence.acquire.gpu;\n}" ::"l"(p), "r"(target) : "memory");
}
__device__ __forceinline__ uint32_t pack_bf16(float lo, float hi) { uint32_t r; asm("cvt.rn.bf16x2.f32 %0, %1, %2;" : "=r"(r) : "f"(hi), "f"(lo)); return r; }
__device__ __forceinline__ float bf_lo(uint32_t v) { return __uint_as_float(v << 16); }
__device__ __forceinline__ float bf_hi(uint32_t v) { return __uint_as_float(v & 0xffff0000u); }
__device__ __forceinline__ float ex2(float x) { float y; asm("ex2.approx.ftz.f32 %0, %1;" : "=f"(y) : "f"(x)); return y; }
__device__ __forceinline__ float rcp(float x) { float y; asm("rcp.approx.ftz.f32 %0, %1;" : "=f"(y) : "f"(x)); return y; }
__device__ __forceinline__ float silu_half(float h) { float y; asm("tanh.approx.f32 %0, %1;" : "=f"(y) : "f"(h)); return fmaf(h, y, h); }
__device__ __forceinline__ float2 lds64f(uint32_t a) { float2 v; asm volatile("ld.shared.v2.f32 {%0,%1}, [%2];" : "=f"(v.x), "=f"(v.y) : "r"(a) : "memory"); return v; }
__device__ __forceinline__ uint4 lds128(uint32_t a) { uint4 v; asm volatile("ld.shared.v4.u32 {%0,%1,%2,%3}, [%4];" : "=r"(v.x), "=r"(v.y), "=r"(v.z), "=r"(v.w) : "r"(a) : "memory"); return v; }
__device__ __forceinline__ void sts128(uint32_t a, uint32_t x, uint32_t y, uint32_t z, uint32_t w) { asm volatile("st.shared.v4.u32 [%0], {%1,%2,%3,%4};" ::"r"(a), "r"(x), "r"(y), "r"(z), "r"(w) : "memory"); }
__device__ __forceinline__ void sts32(uint32_t a, uint32_t x) { asm volatile("st.shared.u32 [%0], %1;" ::"r"(a), "r"(x) : "memory"); }
__device__ __forceinline__ void sts32p(uint32_t a, uint32_t x, uint32_t p) { asm volatile("{\n.reg .pred q;\nsetp.ne.u32 q, %2, 0;\n@q st.shared.u32 [%0], %1;\n}" ::"r"(a), "r"(x), "r"(p) : "memory"); }
__device__ __forceinline__ void sts32f(uint32_t a, float x) { asm volatile("st.shared.f32 [%0], %1;" ::"r"(a), "f"(x) : "memory"); }
__device__ __forceinline__ void sts64f(uint32_t a, float x, float y) { asm volatile("st.shared.v2.f32 [%0], {%1,%2};" ::"r"(a), "f"(x), "f"(y) : "memory"); }
__device__ __forceinline__ float lds32f(uint32_t a) { float v; asm volatile("ld.shared.f32 %0, [%1];" : "=f"(v) : "r"(a) : "memory"); return v; }
__device__ __forceinline__ void sts16(uint32_t a, uint16_t x) { asm volatile("st.shared.u16 [%0], %1;" ::"r"(a), "h"(x) : "memory"); }
__device__ __forceinline__ void stsm4(uint32_t a, uint32_t r0, uint32_t r1, uint32_t r2, uint32_t r3) {
  asm volatile("stmatrix.sync.aligned.m8n8.x4.shared.b16 [%0], {%1,%2,%3,%4};" ::"r"(a), "r"(r0), "r"(r1), "r"(r2), "r"(r3) : "memory");
}
__device__ __forceinline__ void ldsm4t(uint32_t a, uint32_t& r0, uint32_t& r1, uint32_t& r2, uint32_t& r3) {
  asm volatile("ldmatrix.sync.aligned.m8n8.x4.trans.shared.b16 {%0,%1,%2,%3}, [%4];" : "=r"(r0), "=r"(r1), "=r"(r2), "=r"(r3) : "r"(a) : "memory");
}
__device__ __forceinline__ void ldsm2t(uint32_t a, uint32_t& r0, uint32_t& r1) {
  asm volatile("ldmatrix.sync.aligned.m8n8.x2.trans.shared.b16 {%0,%1}, [%2];" : "=r"(r0), "=r"(r1) : "r"(a) : "memory");
}
__device__ __forceinline__ void ldsm4(uint32_t a, uint32_t& r0, uint32_t& r1, uint32_t& r2, uint32_t& r3) {
  asm volatile("ldmatrix.sync.aligned.m8n8.x4.shared.b16 {%0,%1,%2,%3}, [%4];" : "=r"(r0), "=r"(r1), "=r"(r2), "=r"(r3) : "r"(a) : "memory");
}
__device__ __forceinline__ void ldsm2(uint32_t a, uint32_t& r0, uint32_t& r1) {
  asm volatile("ldmatrix.sync.aligned.m8n8.x2.shared.b16 {%0,%1}, [%2];" : "=r"(r0), "=r"(r1) : "r"(a) : "memory");
}
__device__ __forceinline__ void mma1688(float (&c)[4], uint32_t a0, uint32_t a1, uint32_t b0) {
  asm("mma.sync.aligned.m16n8k8.row.col.f32.bf16.bf16.f32 {%0,%1,%2,%3}, {%4,%5}, {%6}, {%0,%1,%2,%3};"
      : "+f"(c[0]), "+f"(c[1]), "+f"(c[2]), "+f"(c[3]) : "r"(a0), "r"(a1), "r"(b0));
}
__device__ __forceinline__ void mma16816(float (&c)[4], uint32_t a0, uint32_t a1, uint32_t a2, uint32_t a3, uint32_t b0, uint32_t b1) {
  asm("mma.sync.aligned.m16n8k16.row.col.f32.bf16.bf16.f32 {%0,%1,%2,%3}, {%4,%5,%6,%7}, {%8,%9}, {%0,%1,%2,%3};"
               : "+f"(c[0]), "+f"(c[1]), "+f"(c[2]), "+f"(c[3]) : "r"(a0), "r"(a1), "r"(a2), "r"(a3), "r"(b0), "r"(b1));
}
__device__ __forceinline__ uint4 ldg_nc128(const void* p) { uint4 v; asm volatile("ld.global.nc.L1::no_allocate.v4.u32 {%0,%1,%2,%3}, [%4];" : "=r"(v.x), "=r"(v.y), "=r"(v.z), "=r"(v.w) : "l"(p)); return v; }
__device__ __forceinline__ uint2 ldg_nc64(const void* p) { uint2 v; asm volatile("ld.global.nc.v2.u32 {%0,%1}, [%2];" : "=r"(v.x), "=r"(v.y) : "l"(p)); return v; }
__device__ __forceinline__ uint32_t ldg_nc32(const void* p) { uint32_t v; asm volatile("ld.global.nc.u32 %0, [%1];" : "=r"(v) : "l"(p)); return v; }
__device__ __forceinline__ float4 ldg_cg128f(const void* p) { float4 v; asm volatile("ld.global.cg.v4.f32 {%0,%1,%2,%3}, [%4];" : "=f"(v.x), "=f"(v.y), "=f"(v.z), "=f"(v.w) : "l"(p) : "memory"); return v; }
__device__ __forceinline__ float2 ldg_cg64f(const void* p) { float2 v; asm volatile("ld.global.cg.v2.f32 {%0,%1}, [%2];" : "=f"(v.x), "=f"(v.y) : "l"(p) : "memory"); return v; }
__device__ __forceinline__ uint4 ld_relaxed128(const void* p) { uint4 v; asm volatile("ld.relaxed.gpu.global.v4.u32 {%0,%1,%2,%3}, [%4];" : "=r"(v.x), "=r"(v.y), "=r"(v.z), "=r"(v.w) : "l"(p) : "memory"); return v; }
__device__ __forceinline__ uint4 ld_tagged2(const void* p) {
  uint64_t a, b; asm volatile("ld.relaxed.gpu.global.v2.b64 {%0,%1}, [%2];" : "=l"(a), "=l"(b) : "l"(p) : "memory");
  return make_uint4((uint32_t)a, (uint32_t)(a >> 32), (uint32_t)b, (uint32_t)(b >> 32));
}
__device__ __forceinline__ void st_tagged2(void* p, uint32_t a, uint32_t b, uint32_t tag) {
  asm volatile("st.relaxed.gpu.global.v2.b64 [%0], {%1,%2};" ::"l"(p), "l"(((uint64_t)tag << 32) | a), "l"(((uint64_t)tag << 32) | b) : "memory");
}
__device__ __forceinline__ void st_relaxed128(void* p, uint32_t a, uint32_t b, uint32_t c, uint32_t d) { asm volatile("st.relaxed.gpu.global.v4.u32 [%0], {%1,%2,%3,%4};" ::"l"(p), "r"(a), "r"(b), "r"(c), "r"(d) : "memory"); }
__device__ __forceinline__ void stg32(void* p, uint32_t v) { asm volatile("st.global.u32 [%0], %1;" ::"l"(p), "r"(v) : "memory"); }
__device__ __forceinline__ void stg128f(void* p, float a, float b, float c, float d) { asm volatile("st.global.v4.f32 [%0], {%1,%2,%3,%4};" ::"l"(p), "f"(a), "f"(b), "f"(c), "f"(d) : "memory"); }

__device__ __forceinline__ void wgmma_ss(float (&d)[40], uint64_t da, uint64_t db, int sd) {
  asm volatile("{\n.reg .pred p;\nsetp.ne.b32 p, %42, 0;\nwgmma.mma_async.sync.aligned.m64n80k16.f32.bf16.bf16 {%0, %1, %2, %3, %4, %5, %6, %7, %8, %9, %10, %11, %12, %13, %14, %15, %16, %17, %18, %19, %20, %21, %22, %23, %24, %25, %26, %27, %28, %29, %30, %31, %32, %33, %34, %35, %36, %37, %38, %39}, %40, %41, p, 1, 1, 0, 1;\n}"
    : "+f"(d[0]), "+f"(d[1]), "+f"(d[2]), "+f"(d[3]), "+f"(d[4]), "+f"(d[5]), "+f"(d[6]), "+f"(d[7]), "+f"(d[8]), "+f"(d[9]), "+f"(d[10]), "+f"(d[11]), "+f"(d[12]), "+f"(d[13]), "+f"(d[14]), "+f"(d[15]), "+f"(d[16]), "+f"(d[17]), "+f"(d[18]), "+f"(d[19]), "+f"(d[20]), "+f"(d[21]), "+f"(d[22]), "+f"(d[23]), "+f"(d[24]), "+f"(d[25]), "+f"(d[26]), "+f"(d[27]), "+f"(d[28]), "+f"(d[29]), "+f"(d[30]), "+f"(d[31]), "+f"(d[32]), "+f"(d[33]), "+f"(d[34]), "+f"(d[35]), "+f"(d[36]), "+f"(d[37]), "+f"(d[38]), "+f"(d[39]) : "l"(da), "l"(db), "r"(sd));
}
__device__ __forceinline__ void wgmma_ss(float (&d)[44], uint64_t da, uint64_t db, int sd) {
  asm volatile("{\n.reg .pred p;\nsetp.ne.b32 p, %46, 0;\nwgmma.mma_async.sync.aligned.m64n88k16.f32.bf16.bf16 {%0, %1, %2, %3, %4, %5, %6, %7, %8, %9, %10, %11, %12, %13, %14, %15, %16, %17, %18, %19, %20, %21, %22, %23, %24, %25, %26, %27, %28, %29, %30, %31, %32, %33, %34, %35, %36, %37, %38, %39, %40, %41, %42, %43}, %44, %45, p, 1, 1, 0, 1;\n}"
    : "+f"(d[0]), "+f"(d[1]), "+f"(d[2]), "+f"(d[3]), "+f"(d[4]), "+f"(d[5]), "+f"(d[6]), "+f"(d[7]), "+f"(d[8]), "+f"(d[9]), "+f"(d[10]), "+f"(d[11]), "+f"(d[12]), "+f"(d[13]), "+f"(d[14]), "+f"(d[15]), "+f"(d[16]), "+f"(d[17]), "+f"(d[18]), "+f"(d[19]), "+f"(d[20]), "+f"(d[21]), "+f"(d[22]), "+f"(d[23]), "+f"(d[24]), "+f"(d[25]), "+f"(d[26]), "+f"(d[27]), "+f"(d[28]), "+f"(d[29]), "+f"(d[30]), "+f"(d[31]), "+f"(d[32]), "+f"(d[33]), "+f"(d[34]), "+f"(d[35]), "+f"(d[36]), "+f"(d[37]), "+f"(d[38]), "+f"(d[39]), "+f"(d[40]), "+f"(d[41]), "+f"(d[42]), "+f"(d[43]) : "l"(da), "l"(db), "r"(sd));
}
__device__ __forceinline__ void wgmma_ss(float (&d)[64], uint64_t da, uint64_t db, int sd) {
  asm volatile("{\n.reg .pred p;\nsetp.ne.b32 p, %66, 0;\nwgmma.mma_async.sync.aligned.m64n128k16.f32.bf16.bf16 {%0, %1, %2, %3, %4, %5, %6, %7, %8, %9, %10, %11, %12, %13, %14, %15, %16, %17, %18, %19, %20, %21, %22, %23, %24, %25, %26, %27, %28, %29, %30, %31, %32, %33, %34, %35, %36, %37, %38, %39, %40, %41, %42, %43, %44, %45, %46, %47, %48, %49, %50, %51, %52, %53, %54, %55, %56, %57, %58, %59, %60, %61, %62, %63}, %64, %65, p, 1, 1, 0, 1;\n}"
    : "+f"(d[0]), "+f"(d[1]), "+f"(d[2]), "+f"(d[3]), "+f"(d[4]), "+f"(d[5]), "+f"(d[6]), "+f"(d[7]), "+f"(d[8]), "+f"(d[9]), "+f"(d[10]), "+f"(d[11]), "+f"(d[12]), "+f"(d[13]), "+f"(d[14]), "+f"(d[15]), "+f"(d[16]), "+f"(d[17]), "+f"(d[18]), "+f"(d[19]), "+f"(d[20]), "+f"(d[21]), "+f"(d[22]), "+f"(d[23]), "+f"(d[24]), "+f"(d[25]), "+f"(d[26]), "+f"(d[27]), "+f"(d[28]), "+f"(d[29]), "+f"(d[30]), "+f"(d[31]), "+f"(d[32]), "+f"(d[33]), "+f"(d[34]), "+f"(d[35]), "+f"(d[36]), "+f"(d[37]), "+f"(d[38]), "+f"(d[39]), "+f"(d[40]), "+f"(d[41]), "+f"(d[42]), "+f"(d[43]), "+f"(d[44]), "+f"(d[45]), "+f"(d[46]), "+f"(d[47]), "+f"(d[48]), "+f"(d[49]), "+f"(d[50]), "+f"(d[51]), "+f"(d[52]), "+f"(d[53]), "+f"(d[54]), "+f"(d[55]), "+f"(d[56]), "+f"(d[57]), "+f"(d[58]), "+f"(d[59]), "+f"(d[60]), "+f"(d[61]), "+f"(d[62]), "+f"(d[63]) : "l"(da), "l"(db), "r"(sd));
}
__device__ __forceinline__ void wgmma_ss(float (&d)[80], uint64_t da, uint64_t db, int sd) {
  asm volatile("{\n.reg .pred p;\nsetp.ne.b32 p, %82, 0;\nwgmma.mma_async.sync.aligned.m64n160k16.f32.bf16.bf16 {%0, %1, %2, %3, %4, %5, %6, %7, %8, %9, %10, %11, %12, %13, %14, %15, %16, %17, %18, %19, %20, %21, %22, %23, %24, %25, %26, %27, %28, %29, %30, %31, %32, %33, %34, %35, %36, %37, %38, %39, %40, %41, %42, %43, %44, %45, %46, %47, %48, %49, %50, %51, %52, %53, %54, %55, %56, %57, %58, %59, %60, %61, %62, %63, %64, %65, %66, %67, %68, %69, %70, %71, %72, %73, %74, %75, %76, %77, %78, %79}, %80, %81, p, 1, 1, 0, 1;\n}"
    : "+f"(d[0]), "+f"(d[1]), "+f"(d[2]), "+f"(d[3]), "+f"(d[4]), "+f"(d[5]), "+f"(d[6]), "+f"(d[7]), "+f"(d[8]), "+f"(d[9]), "+f"(d[10]), "+f"(d[11]), "+f"(d[12]), "+f"(d[13]), "+f"(d[14]), "+f"(d[15]), "+f"(d[16]), "+f"(d[17]), "+f"(d[18]), "+f"(d[19]), "+f"(d[20]), "+f"(d[21]), "+f"(d[22]), "+f"(d[23]), "+f"(d[24]), "+f"(d[25]), "+f"(d[26]), "+f"(d[27]), "+f"(d[28]), "+f"(d[29]), "+f"(d[30]), "+f"(d[31]), "+f"(d[32]), "+f"(d[33]), "+f"(d[34]), "+f"(d[35]), "+f"(d[36]), "+f"(d[37]), "+f"(d[38]), "+f"(d[39]), "+f"(d[40]), "+f"(d[41]), "+f"(d[42]), "+f"(d[43]), "+f"(d[44]), "+f"(d[45]), "+f"(d[46]), "+f"(d[47]), "+f"(d[48]), "+f"(d[49]), "+f"(d[50]), "+f"(d[51]), "+f"(d[52]), "+f"(d[53]), "+f"(d[54]), "+f"(d[55]), "+f"(d[56]), "+f"(d[57]), "+f"(d[58]), "+f"(d[59]), "+f"(d[60]), "+f"(d[61]), "+f"(d[62]), "+f"(d[63]), "+f"(d[64]), "+f"(d[65]), "+f"(d[66]), "+f"(d[67]), "+f"(d[68]), "+f"(d[69]), "+f"(d[70]), "+f"(d[71]), "+f"(d[72]), "+f"(d[73]), "+f"(d[74]), "+f"(d[75]), "+f"(d[76]), "+f"(d[77]), "+f"(d[78]), "+f"(d[79]) : "l"(da), "l"(db), "r"(sd));
}
__device__ __forceinline__ void wgmma_rs(float (&d)[40], uint32_t a0, uint32_t a1, uint32_t a2, uint32_t a3, uint64_t db, int sd) {
  asm volatile("{\n.reg .pred p;\nsetp.ne.b32 p, %45, 0;\nwgmma.mma_async.sync.aligned.m64n80k16.f32.bf16.bf16 {%0, %1, %2, %3, %4, %5, %6, %7, %8, %9, %10, %11, %12, %13, %14, %15, %16, %17, %18, %19, %20, %21, %22, %23, %24, %25, %26, %27, %28, %29, %30, %31, %32, %33, %34, %35, %36, %37, %38, %39}, {%40, %41, %42, %43}, %44, p, 1, 1, 1;\n}"
    : "+f"(d[0]), "+f"(d[1]), "+f"(d[2]), "+f"(d[3]), "+f"(d[4]), "+f"(d[5]), "+f"(d[6]), "+f"(d[7]), "+f"(d[8]), "+f"(d[9]), "+f"(d[10]), "+f"(d[11]), "+f"(d[12]), "+f"(d[13]), "+f"(d[14]), "+f"(d[15]), "+f"(d[16]), "+f"(d[17]), "+f"(d[18]), "+f"(d[19]), "+f"(d[20]), "+f"(d[21]), "+f"(d[22]), "+f"(d[23]), "+f"(d[24]), "+f"(d[25]), "+f"(d[26]), "+f"(d[27]), "+f"(d[28]), "+f"(d[29]), "+f"(d[30]), "+f"(d[31]), "+f"(d[32]), "+f"(d[33]), "+f"(d[34]), "+f"(d[35]), "+f"(d[36]), "+f"(d[37]), "+f"(d[38]), "+f"(d[39]) : "r"(a0), "r"(a1), "r"(a2), "r"(a3), "l"(db), "r"(sd));
}
__device__ __forceinline__ void wgmma_rs0(float (&d)[40], uint32_t a0, uint32_t a1, uint32_t a2, uint32_t a3, uint64_t db) {
  asm volatile("{\n.reg .pred p;\nsetp.ne.b32 p, 0, 0;\nwgmma.mma_async.sync.aligned.m64n80k16.f32.bf16.bf16 {%0, %1, %2, %3, %4, %5, %6, %7, %8, %9, %10, %11, %12, %13, %14, %15, %16, %17, %18, %19, %20, %21, %22, %23, %24, %25, %26, %27, %28, %29, %30, %31, %32, %33, %34, %35, %36, %37, %38, %39}, {%40, %41, %42, %43}, %44, p, 1, 1, 1;\n}"
    : "=f"(d[0]), "=f"(d[1]), "=f"(d[2]), "=f"(d[3]), "=f"(d[4]), "=f"(d[5]), "=f"(d[6]), "=f"(d[7]), "=f"(d[8]), "=f"(d[9]), "=f"(d[10]), "=f"(d[11]), "=f"(d[12]), "=f"(d[13]), "=f"(d[14]), "=f"(d[15]), "=f"(d[16]), "=f"(d[17]), "=f"(d[18]), "=f"(d[19]), "=f"(d[20]), "=f"(d[21]), "=f"(d[22]), "=f"(d[23]), "=f"(d[24]), "=f"(d[25]), "=f"(d[26]), "=f"(d[27]), "=f"(d[28]), "=f"(d[29]), "=f"(d[30]), "=f"(d[31]), "=f"(d[32]), "=f"(d[33]), "=f"(d[34]), "=f"(d[35]), "=f"(d[36]), "=f"(d[37]), "=f"(d[38]), "=f"(d[39]) : "r"(a0), "r"(a1), "r"(a2), "r"(a3), "l"(db));
}

#define CLUSTER_ARRIVE() asm volatile("barrier.cluster.arrive.relaxed.aligned;" ::: "memory")
#define CLUSTER_WAIT() asm volatile("barrier.cluster.wait.aligned;" ::: "memory")

__device__ __forceinline__ void ring_item(uint32_t dst, const CUtensorMap* m0, int col, int row, uint32_t bar, uint32_t bytes) {
  mbar_expect_tx(bar, bytes);
  tma3d_mc(dst, m0, col, row, bar);
  tma2d_mc(dst + 4096, m0 + 1, col + 64, row, bar);
}

struct Rel {
  uint32_t base; bool on;
  __device__ __forceinline__ Rel(uint32_t sb, int tid) {
    asm volatile("mapa.shared::cluster.u32 %0, %1, %2;" : "=r"(base) : "r"(sb), "r"((tid >> 5) & 1));
    on = (tid & 95) == 0;
  }
  __device__ __forceinline__ void operator()(uint32_t off) const {
    if (on) asm volatile("mbarrier.arrive.shared::cluster.b64 _, [%0];" ::"r"(base + off) : "memory");
  }
};

template <int R>
__device__ __forceinline__ void tile_loop(float (&a0)[R], float (&a1)[R], uint32_t sb, uint32_t fbar, uint32_t& ph, uint32_t& so, int k0, int k1,
                                          const Rel& rel, uint32_t& prev_r, uint32_t& prev_x, uint32_t xrel_step, int ksig, int sid, uint32_t clk0) {
  uint64_t da = mkdesc(sb + k0 * 16384, 16, 1024, 1);
  const uint64_t db0 = mkdesc(sb + RING_OFF, 2048, 512, 2);
  uint32_t cur_x = xrel_step ? BAR_X + 8 * k0 : BAR_DUMMY;
#pragma unroll 1
  for (int k = k0; k < k1; k++) {
    const uint64_t db = db0 + so * (SLOT / 16);
    mbar_wait(sb + fbar + 24 + 8 * so, (ph >> so) & 1);
    STAMP2_IF((threadIdx.x & 127) == 0, sid + k);
    wg_fence();
    wgmma_ss(a0, da, db, k); wgmma_ss(a1, da + 512, db, k);
    wg_commit();
    wg_wait<1>();
    rel(prev_r); rel(prev_x);
    wgmma_ss(a0, da + 2, db + 64, 1); wgmma_ss(a1, da + 514, db + 64, 1);
    wgmma_ss(a0, da + 4, db + 384, 1); wgmma_ss(a1, da + 516, db + 384, 1);
    wgmma_ss(a0, da + 6, db + 448, 1); wgmma_ss(a1, da + 518, db + 448, 1);
    wg_commit();
    ph ^= 1u << so;
    prev_r = BAR_RE + 24 + 8 * so; prev_x = cur_x; cur_x += xrel_step;
    so = so == 4 ? 0 : so + 1; da += 1024;
  }
}

__device__ __forceinline__ void fetch_cs(uint32_t sb, int c, int lane, unsigned tag, int u0, int u1) {
  const int ua = u0 + lane, ub = min(u0 + 32 + lane, u1 - 1);
  uint4 va, vb;
#pragma unroll 1
  for (int tries = 0; tries < (1 << 16); tries++) {
    va = ld_tagged2(g_colsum + c * 228 + ua); vb = ld_tagged2(g_colsum + c * 228 + ub);
    if (va.y == tag && va.w == tag && vb.y == tag && vb.w == tag) break;
  }
  sts64f(sb + CS_OFF + ua * 8, __uint_as_float(va.x), __uint_as_float(va.z));
  sts64f(sb + CS_OFF + ub * 8, __uint_as_float(vb.x), __uint_as_float(vb.z));
}

struct RowStats { float mean[2][2], rstd[2][2]; };
__device__ __forceinline__ void load_stats(RowStats& st, uint32_t sb, int w, int g) {
#pragma unroll
  for (int m = 0; m < 2; m++)
#pragma unroll
    for (int i = 0; i < 2; i++) {
      float2 v = lds64f(sb + ST_OFF + (64 * m + 16 * w + 8 * i + g) * 8);
      st.mean[m][i] = v.x; st.rstd[m][i] = v.y;
    }
}

template <int R>
__device__ __forceinline__ void epi_h(float (&a0)[R], float (&a1)[R], uint32_t (&o)[R], uint32_t sb, int cs_off, int w, int lane, uint32_t zero) {
  RowStats st; load_stats(st, sb, w, lane >> 2);
#pragma unroll
  for (int m = 0; m < 2; m++) { st.rstd[m][0] *= 0.5f; st.rstd[m][1] *= 0.5f; }
  const uint32_t ca = sb + CS_OFF + (cs_off + 2 * (lane & 3)) * 4;
#pragma unroll
  for (int j = 0; j < R / 4; j++) {
    const int d = j >= E1_DIST ? 4 * (j - E1_DIST) : 0;
    const float2 cs = lds64f((j >= E1_DIST ? (ca | (o[d] & o[d + 1] & o[d + 2] & o[d + 3] & zero)) : ca) + j * 32);
#pragma unroll
    for (int i = 0; i < 2; i++) {
      o[4 * j + i] = pack_bf16(silu_half(fmaf(-st.mean[0][i], cs.x, a0[4 * j + 2 * i]) * st.rstd[0][i]), silu_half(fmaf(-st.mean[0][i], cs.y, a0[4 * j + 2 * i + 1]) * st.rstd[0][i]));
      o[4 * j + 2 + i] = pack_bf16(silu_half(fmaf(-st.mean[1][i], cs.x, a1[4 * j + 2 * i]) * st.rstd[1][i]), silu_half(fmaf(-st.mean[1][i], cs.y, a1[4 * j + 2 * i + 1]) * st.rstd[1][i]));
    }
  }
#pragma unroll
  for (int i = 0; i < R; i++) asm volatile("" : "+r"(o[i])::"memory");
}
template <int R, int I0, int I1, int PACE = 0>
__device__ __forceinline__ void store_h(const uint32_t (&o)[R], char* hp) {
  uint32_t tn = PACE ? (uint32_t)clock() : 0;
#pragma unroll
  for (int i = I0; i < I1; i++) {
    if (PACE && (i - I0) % PGRP == 0) { while ((int)((uint32_t)clock() - tn) < 0) {} tn += PACE; }
    stg32(hp + (i >> 2) * 2048 + (i & 1) * 128 + ((i >> 1) & 1) * 1024, o[i]);
  }
}

__device__ __forceinline__ void fix_pack(float (&a0)[40], float (&a1)[40], uint32_t (&f0)[20], uint32_t (&f1)[20], const RowStats& st, uint32_t cs_addr) {
#pragma unroll
  for (int j = 0; j < 10; j++) {
    float2 cs = lds64f(cs_addr + j * 32);
#pragma unroll
    for (int i = 0; i < 2; i++) {
      float u0 = fmaf(-st.mean[0][i], cs.x, a0[4 * j + 2 * i]), u1 = fmaf(-st.mean[0][i], cs.y, a0[4 * j + 2 * i + 1]);
      float u2 = fmaf(-st.mean[1][i], cs.x, a1[4 * j + 2 * i]), u3 = fmaf(-st.mean[1][i], cs.y, a1[4 * j + 2 * i + 1]);
      f0[2 * j + i] = pack_bf16(u0, u1);
      f1[2 * j + i] = pack_bf16(u2, u3);
    }
  }
}

__device__ __forceinline__ void phi_gemm(float (&p)[40], uint32_t (&f)[20], uint32_t sb) {
  uint64_t db = mkdesc(sb + WPHI_OFF, 1280, 128, 0);
#pragma unroll
  for (int kk = 0; kk < 5; kk++) {
    if (kk == 0) wgmma_rs0(p, f[0], f[1], f[2], f[3], db);
    else wgmma_rs(p, f[4 * kk], f[4 * kk + 1], f[4 * kk + 2], f[4 * kk + 3], db + kk * 160, 1);
  }
  wg_commit();
}

__device__ __forceinline__ uint32_t badd2(uint32_t a, uint32_t b) { uint32_t r; asm("add.rn.bf16x2 %0, %1, %2;" : "=r"(r) : "r"(a), "r"(b)); return r; }
__device__ __forceinline__ uint32_t bmul2(uint32_t a, uint32_t b) { uint32_t r; asm("mul.rn.bf16x2 %0, %1, %2;" : "=r"(r) : "r"(a), "r"(b)); return r; }
__device__ __forceinline__ void softmax_part(const float (&p)[40], int i, float s, float b, uint32_t (&o)[20], int off) {
  float e[20];
#pragma unroll
  for (int j = 0; j < 10; j++) { e[2 * j] = ex2(fmaf(p[4 * j + 2 * i], s, b)); e[2 * j + 1] = ex2(fmaf(p[4 * j + 2 * i + 1], s, b)); }
  uint32_t q[10];
#pragma unroll
  for (int j = 0; j < 10; j++) q[j] = pack_bf16(e[2 * j], e[2 * j + 1]);
  const uint32_t t0 = badd2(badd2(badd2(q[0], q[1]), badd2(q[2], q[3])), q[8]), t1 = badd2(badd2(badd2(q[4], q[5]), badd2(q[6], q[7])), q[9]);
  const float r = rcp((bf_lo(t0) + bf_hi(t0)) + (bf_lo(t1) + bf_hi(t1)));
  const uint32_t r2 = pack_bf16(r, r);
#pragma unroll
  for (int j = 0; j < 10; j++) o[off + j] = bmul2(q[j], r2);
}
__device__ __forceinline__ void dual_softmax(const float (&p)[40], int i, float sc, uint32_t (&o)[20]) {
  float mx = p[2 * i], mn = p[2 * i], mx2 = p[2 * i + 1], mn2 = p[2 * i + 1];
#pragma unroll
  for (int j = 1; j < 10; j++) { mx = fmaxf(mx, p[4 * j + 2 * i]); mn = fminf(mn, p[4 * j + 2 * i]); mx2 = fmaxf(mx2, p[4 * j + 2 * i + 1]); mn2 = fminf(mn2, p[4 * j + 2 * i + 1]); }
  softmax_part(p, i, sc, -fmaxf(mx, mx2) * sc, o, 0);
  softmax_part(p, i, -sc, fminf(mn, mn2) * sc, o, 10);
}
__device__ __forceinline__ void store_phi_if(uint32_t a, const uint32_t (&o)[20], int p) {
#pragma unroll
  for (int v = 0; v < 5; v++)
    asm volatile("{\n.reg .pred q;\nsetp.ne.u32 q, %5, 0;\n@q st.shared.v4.u32 [%0], {%1,%2,%3,%4};\n}" ::"r"(a + v * 16), "r"(o[4 * v]), "r"(o[4 * v + 1]), "r"(o[4 * v + 2]), "r"(o[4 * v + 3]), "r"(p) : "memory");
}
__device__ __forceinline__ void store_phi(uint32_t a, const uint32_t (&o)[20]) {
#pragma unroll
  for (int v = 0; v < 5; v++) sts128(a + v * 16, o[4 * v], o[4 * v + 1], o[4 * v + 2], o[4 * v + 3]);
}

__global__ void __cluster_dims__(2, 1, 1) __launch_bounds__(384, 1)
fused_kernel(const __nv_bfloat16* __restrict__ x, const __nv_bfloat16* __restrict__ wqkv,
             const __nv_bfloat16* __restrict__ wphi, const __nv_bfloat16* __restrict__ w1, const __nv_bfloat16* __restrict__ w2,
             const __nv_bfloat16* __restrict__ wo, const __grid_constant__ Maps maps) {
  extern __shared__ __align__(1024) uint8_t smem_raw[];
  const uint32_t clk0 = (uint32_t)clock();
  if (threadIdx.x >= 320) {
    const uint32_t ln = threadIdx.x & 31, kk = (threadIdx.x >> 5) & 1, b = blockIdx.x & 127;
    const char* base = ln < 16 ? (const char*)x : ln < 24 ? (const char*)w1 : (const char*)wqkv;
    const uint32_t off = ln < 16 ? (b * 16 + ln) * 1280 + kk * 128 : ((b >> 1) + kk * 64) * (ln < 24 ? 3456 : 3840) + (ln < 24 ? (b & 1) * 1024 + (ln - 16) * 128 : 2560 + (b & 1) * 640 + min(ln - 24, 4u) * 128);
    prefetch_l2(base + off);
  } else if (threadIdx.x == 288) {
    prefetch_map(&maps.x); prefetch_map(&maps.w1a); prefetch_map(&maps.q32); prefetch_map(&maps.q16);
  }
  const uint32_t sb = __shfl_sync(0xffffffffu, smem_u32(smem_raw), 0);
  const int warp = __shfl_sync(0xffffffffu, threadIdx.x >> 5, 0);
  const int lane = threadIdx.x & 31;
  if (warp < 9) {
    const int j = warp == 8 ? 0 : warp + 1;
    if (elect_one()) {
      const uint32_t cnt = ((USE_MC ? 0x211111444ull : 0x111111222ull) >> (4 * j)) & 15;
#pragma unroll
      for (int e = 0; e < 4; e++) mbar_init(sb + BAR_X + 32 * j + 8 * e, cnt);
      if (warp < 5) {
#pragma unroll
        for (int e = 0; e < 4; e++) mbar_init(sb + BAR_RE + 32 + 32 * warp + 8 * e, warp < 2 ? NCTA_MC : warp == 4 ? 1 : 2);
      }
      asm volatile("fence.mbarrier_init.release.cluster;" ::: "memory");
    }
    __syncwarp();
  }
  CLUSTER_ARRIVE();
  int lp;
  { const int i = blockIdx.x >> 1; lp = i < 4 ? 39 + 8 * i : i < 36 ? i - 4 : i < 64 ? 32 + ((i - 36) / 7) * 8 + (i - 36) % 7 : i; }
  const int bid = 2 * lp + (blockIdx.x & 1);
  if (bid >= 128) {
    const int e = bid - 128;
    CLUSTER_WAIT();
    const uint32_t fb = sb + CS_OFF, eb = fb + 96, red = sb + 12 * 16384;
    if (elect_one()) { mbar_init(fb + 8 * warp, 1); mbar_init(eb + 8 * warp, 8); asm volatile("fence.mbarrier_init.release.cluster;" ::: "memory"); }
    __syncthreads();
    if (warp == 8) {
      uint32_t s = 0, par = 1;
#pragma unroll 1
      for (int b = e; b < 57; b += 4) {
        const bool isw = b < 16 || (b >= 26 && b < 37);
        const int col = 64 * (b < 16 ? b : b < 26 ? b - 6 : b < 37 ? b - 10 : b < 47 ? b - 37 : b - 27);
#pragma unroll 1
        for (int row = 0; row < 640; row += 128) {
          mbar_wait(eb + 8 * s, par);
          if (elect_one()) { mbar_expect_tx(fb + 8 * s, 16384); tma2d(sb + s * 16384, isw ? &maps.jw : &maps.jq, col, row, fb + 8 * s); }
          if (++s == 12) { s = 0; par ^= 1; }
        }
      }
    } else if (warp < 8) {
      unsigned tag = 0;
      if (threadIdx.x == 0) { asm volatile("atom.relaxed.gpu.global.add.u32 %0, [%1], 32;" : "=r"(tag) : "l"(g_pro) : "memory"); sts32(red + 4096, (tag >> 8) + 1); }
      const int g = lane >> 2, t = lane & 3;
      const uint32_t sel0 = g == 0 ? 0x00003F80u : g == 1 ? 0x3F800000u : 0u, sel1 = g == 2 ? 0x00003F80u : g == 3 ? 0x3F800000u : 0u;
      const uint32_t a0 = sb + (16 * warp + 2 * t) * 128 + ((g ^ (2 * t)) << 4), a1 = sb + (16 * warp + 2 * t + 1) * 128 + ((g ^ (2 * t + 1)) << 4);
      uint32_t s = 0, par = 0, rb = 0;
#pragma unroll 1
      for (int b = e; b < 57; b += 4) {
        float c0[4] = {0.f, 0.f, 0.f, 0.f}, c1[4] = {0.f, 0.f, 0.f, 0.f};
#pragma unroll 1
        for (int i = 0; i < 5; i++) {
          mbar_wait(fb + 8 * s, par);
          const uint4 v0 = lds128(a0 + s * 16384), v1 = lds128(a1 + s * 16384), v2 = lds128(a0 + s * 16384 + 1024), v3 = lds128(a1 + s * 16384 + 1024);
          mma16816(c0, v0.x, v0.y, v0.z, v0.w, sel0, sel1); mma16816(c1, v1.x, v1.y, v1.z, v1.w, sel0, sel1);
          mma16816(c0, v2.x, v2.y, v2.z, v2.w, sel0, sel1); mma16816(c1, v3.x, v3.y, v3.z, v3.w, sel0, sel1);
          __syncwarp();
          if (lane == 0) mbar_arrive(eb + 8 * s);
          if (++s == 12) { s = 0; par ^= 1; }
        }
        if (t < 2) sts128(red + rb + (warp * 64 + g * 8 + 4 * t) * 4, __float_as_uint(c0[0] + c1[0]), __float_as_uint(c0[1] + c1[1]), __float_as_uint(c0[2] + c1[2]), __float_as_uint(c0[3] + c1[3]));
        bar_sync(1, 256);
        if (threadIdx.x < 64) {
          float sum = 0.f;
#pragma unroll
          for (int i = 0; i < 8; i++) sum += lds32f(red + rb + (i * 64 + threadIdx.x) * 4);
          int pos;
          if (b < 16) { const int n = 64 * b + threadIdx.x; pos = (n >> 7) * 456 + (n & 127); }
          else if (b >= 26 && b < 37) { const int n = 64 * (b - 26) + threadIdx.x, cc = n / 88; pos = cc * 456 + CS_W1B + (n - cc * 88); }
          else { const int n = 64 * (b < 26 ? b - 16 : b < 47 ? b - 37 : b - 47) + threadIdx.x, cc = n / 80; pos = cc * 456 + (b < 26 ? CS_K : b < 47 ? CS_Q : CS_V) + (n - cc * 80); }
          asm volatile("st.relaxed.gpu.global.b64 [%0], %1;" ::"l"((uint2*)g_colsum + pos), "l"(((uint64_t)__float_as_uint(lds32f(red + 4096)) << 32) | __float_as_uint(sum)) : "memory");
        }
        rb ^= 2048;
      }
    }
    return;
  }
  const uint32_t rank = bid & 1;
  const int pair = bid >> 1;
  const int rg = pair & 7, c = pair >> 3;
  const int r = 2 * rg + rank;
  const int kap = c >> 2, jn = c & 3;

  if (warp >= 8) {
    asm volatile("setmaxnreg.dec.sync.aligned.u32 56;");
    if (warp == 8) {
      if (elect_one()) {
        mbar_arrive_n(sb + BAR_X, 2 * NCTA_MC - 1);
        mbar_expect_tx(sb + BAR_X, 16384);
        tma2d(sb, &maps.x, 0, r * 128, sb + BAR_X);
      }
      __syncwarp();
      STAMP_IF(lane == 0, 58);
      CLUSTER_WAIT();
      {
        const uint32_t dst0 = sb + RING0 + (USE_MC ? rank * 6144 : 0);
        int rowa = 0, rowv = USE_MC ? rank * 32 : 0, kx = 1;
        const int cola = 128 * c + (USE_MC ? 64 * rank : 0), colv = 1280 + 80 * c;
        uint32_t mask = P1_MASK, xmask = P1_XMASK, id = 0, pm = 0xff;
        if (elect_one()) {
          int ra = 0, rv = rowv, kk = 1;
#pragma unroll
          for (int i = 0; i < 8; i++) {
            if ((P1_XMASK >> i) & 1) {
              mbar_arrive_n(sb + BAR_X + 8 * kk, 2 * NCTA_MC - 1);
              mbar_expect_tx(sb + BAR_X + 8 * kk, 16384);
              tma2d(sb + kk * 16384, &maps.x, kk * 64, r * 128, sb + BAR_X + 8 * kk);
              kk++;
            }
            if ((P1_MASK >> i) & 1) { mbar_expect_tx(sb + BAR_RF + 8 * i, 12288); tma2d_mc(dst0 + i * SLOT, &maps.w1a, cola, ra, sb + BAR_RF + 8 * i); ra += 48; }
            else { ring_item(dst0 + i * SLOT, &maps.q32, colv, rv, sb + BAR_RF1 + 8 * i, 10240); rv += 64; }
          }
        }
        __syncwarp();
        rowa = 48 * __builtin_popcount(P1_MASK & 255); rowv += 64 * (8 - __builtin_popcount(P1_MASK & 255)); kx += __builtin_popcount(P1_XMASK & 255);
        mask >>= 8; xmask >>= 8; pm = 0;
#pragma unroll 1
        for (int i = FAST0 ? 8 : 0; i < 24; i++) {
          const uint32_t dst = dst0 + id * SLOT;
          while (((xmask & 1) || (XEARLY && kx >= 8) || (i < XLEADN && kx < 7 && i >= 4)) && kx < 10 && !(kx == 7 && i < 16)) {
            xmask &= ~1u;
            if (kx >= 7) mbar_wait(sb + BAR_RE + 8 * (kx - 7), 1);
            if (elect_one()) {
              mbar_arrive_n(sb + BAR_X + 8 * kx, 2 * NCTA_MC - 1);
              mbar_expect_tx(sb + BAR_X + 8 * kx, 16384);
              tma2d(sb + kx * 16384, &maps.x, kx * 64, r * 128, sb + BAR_X + 8 * kx);
            }
            kx++;
            if (kx < 8) break;
          }
          mbar_wait(sb + BAR_RE + 8 * id, (pm >> id) & 1);
          STAMP2_IF(lane == 0, 64 + i);
          if (mask & 1) {
            if (elect_one()) {
              mbar_expect_tx(sb + BAR_RF + 8 * id, 12288);
              tma2d_mc(dst, &maps.w1a, cola, rowa, sb + BAR_RF + 8 * id);
            }
            rowa = min(rowa + 48, 592);
          } else {
            if (elect_one()) ring_item(dst, &maps.q32, colv, rowv, sb + BAR_RF1 + 8 * id, 10240);
            rowv += 64;
          }
          mask >>= 1; xmask >>= 1;
          pm ^= 1u << id;
          id = id == 7 ? (i < 8 ? 0 : 3) : id + 1;
        }
      }
      {
        const uint32_t dst0 = sb + RING_OFF + (USE_MC ? rank * 6144 : 0);
        uint32_t so = POS_K, pm = ~PH_ALL;
        mbar_wait(sb + BAR_GOK, 0);
        fence_async_global();
#pragma unroll 1
        for (int sec = 0; sec < 3; sec++) {
          const CUtensorMap* m0 = sec == 1 ? &maps.w1_32 : &maps.q32;
          const int col = sec == 1 ? 1024 + 88 * c : (sec == 0 ? 640 : 0) + 80 * c;
          const uint32_t fb = sb + (sec == 1 ? BAR_RF : BAR_RF1) + 24, bytes = sec == 1 ? 11264 : 10240;
          const int rowp = sec == 0 ? -1 : sec == 1 ? 0 : 9;
#pragma unroll 1
          for (int row = USE_MC ? rank * 32 : 0; row < 640; row += 64) {
            const uint32_t dst = dst0 + so * SLOT;
            mbar_wait(sb + BAR_RE + 24 + 8 * so, (pm >> so) & 1);
            STAMP2_IF(lane == 0, 64 + 24 + sec * 10 + (row >> 6));
            if (elect_one()) ring_item(dst, m0, col, row, fb + 8 * so, bytes);
            pm ^= 1u << so; so = so == 4 ? 0 : so + 1;
            if ((row >> 6) == rowp) {
              mbar_wait(sb + BAR_RE + 24 + 8 * 4, (pm >> 4) & 1);
              if (elect_one()) { mbar_expect_tx(sb + BAR_WPHI, 12800); bulk_g2s(sb + WPHI_OFF, g_wphi + c * 800, 12800, sb + BAR_WPHI); }
              pm ^= 16; so = 0;
            }
          }
        }
      }
      {
        unsigned tg; asm volatile("ld.shared.u32 %0, [%1];" : "=r"(tg) : "r"(sb + TAG_OFF) : "memory");
        fetch_cs(sb, c, lane, tg, 188, 228);
      }
      poll_ge(&g_kvc[c * 32], 16);
      STAMP_IF(lane == 0, 35);
      fence_async_global();
      if (elect_one()) { mbar_expect_tx(sb + BAR_KV, 15360); bulk_g2s(sb + V_OFF, g_kv + c * 1920, 15360, sb + BAR_KV); }
      __syncwarp();
    } else if (warp < 11) {
      unsigned tag;
      {
        const int g = lane >> 2, t = lane & 3;
        const int row = r * 128 + c * 16 + (warp - 9) * 8 + g;
        const __nv_bfloat16* xp = x + (size_t)row * kD + 8 * t;
        asm volatile("ld.relaxed.gpu.global.u32 %0, [%1];" : "=r"(tag) : "l"(g_pro) : "memory");
        CLUSTER_WAIT();
        while ((uint32_t)clock() - clk0 < J1_DELAY) {}
        tag = (tag >> 8) + 1;
        if (ST_RESET && t == 0) st_tagged2(g_stats + row, 0u, 0u, tag - 1);
        bar_arrive(6 + (tag & (gridDim.y - 1)), 96);
        float x0 = 0.f, s0 = 0.f, s1 = 0.f, q0 = 0.f, q1 = 0.f;
        const uint32_t xa = sb + (c * 16 + (warp - 9) * 8 + g) * 128;
        const uint32_t xa0 = xa + (((2 * t) ^ g) << 4), xa1 = xa + (((2 * t + 1) ^ g) << 4);
#pragma unroll 1
        for (int k = 0; k < 10; k++) {
          if (CS_IN && k == CS_IN && warp == 10) fetch_cs(sb, c, lane, tag, 0, 64);
          mbar_wait(sb + BAR_X + 8 * k, 0);
          const uint4 v0 = lds128(xa0 + k * 16384), v1 = lds128(xa1 + k * 16384);
          if (k == 0) x0 = __uint_as_float(__float_as_uint(lds32f(xa)) << 16);
          const uint32_t u[8] = {v0.x, v0.y, v0.z, v0.w, v1.x, v1.y, v1.z, v1.w};
#pragma unroll
          for (int e = 0; e < 8; e++) {
            const float d0 = bf_lo(u[e]) - x0, d1 = bf_hi(u[e]) - x0;
            s0 += d0; s1 += d1; q0 = fmaf(d0, d0, q0); q1 = fmaf(d1, d1, q1);
          }
        }
        s0 += s1; q0 += q1;
        s0 += __shfl_xor_sync(0xffffffffu, s0, 1); q0 += __shfl_xor_sync(0xffffffffu, q0, 1);
        s0 += __shfl_xor_sync(0xffffffffu, s0, 2); q0 += __shfl_xor_sync(0xffffffffu, q0, 2);
        const float md = s0 * (1.f / kD);
        if (t == 0) st_tagged2(g_stats + row, __float_as_uint(x0 + md), __float_as_uint(rsqrtf(fmaxf(fmaf(-md, md, q0 * (1.f / kD)), 0.f) + 1e-5f)), tag);
        STAMP_IF(lane == 0 && warp == 9, 0);
      }
      if (warp == 9) {
        {
          uint4 v[4];
#pragma unroll 1
          for (int tries = 0; tries < (1 << 16); tries++) {
#pragma unroll
            for (int i = 0; i < 4; i++) v[i] = ld_tagged2(g_stats + r * 128 + i * 32 + lane);
            if (v[0].y == tag && v[1].y == tag && v[2].y == tag && v[3].y == tag && v[0].w == tag && v[1].w == tag && v[2].w == tag && v[3].w == tag) break;
          }
#pragma unroll
          for (int i = 0; i < 4; i++) sts64f(sb + ST_OFF + (i * 32 + lane) * 8, __uint_as_float(v[i].x), __uint_as_float(v[i].z));
          if (lane == 0) sts32(sb + TAG_OFF, tag);
          bar_arrive(3, CS_HELP ? 96 : 64);
          STAMP_IF(lane == 0, 1);
        }
        mbar_wait(sb + BAR_GOK, 0);
        const char* src = (const char*)g_h + ((size_t)r * 216 + 64 * kap) * 2048;
        poll_ge(&g_ha[(r * 2 + kap) * 32], 4);
        fence_async_global();
        STAMP_IF(lane == 0, 40);
        uint32_t bo = 0, par = 0;
#pragma unroll 1
        for (int q = 0; q < 14; q++) {
          if (q == 8) {
            poll_ge(&g_hb[(r * 2 + kap) * 32], 4);
            fence_async_global();
            src += (64 - 20 * kap) * 2048;
            STAMP_IF(lane == 0, 41);
          }
          if (q < 4) mbar_wait(sb + BAR_X + 8 * ((XG_A >> (4 * q)) & 15), 1);
          else mbar_wait(sb + BAR_BE + bo, par);
          STAMP2_IF(lane == 0, 216 + q);
          const uint32_t bytes = q < 13 ? 16384 : 8192;
          if (elect_one()) { mbar_expect_tx(sb + BAR_BF + bo, bytes); bulk_g2s(sb + bo * (BUF_BYTES / 8), src, bytes, sb + BAR_BF + bo); }
          src += 16384;
          bo = (bo + 8) & 24; par ^= (bo == 0 && q > 3);
        }
        src = (const char*)g_o + (size_t)(r * 2 + kap) * 81920;
        const unsigned* fp = &g_oc[(r * 8 + ((lane + ROT * c) & 7)) * 32];
        const int own = ROT ? 0 : c;
        uint32_t ready = 1u << own, p0 = 0, p1 = 0, p2 = 0; (void)p0; (void)p1; (void)p2;
#pragma unroll 1
        for (int j = 0; j < 8; j++) {
          if (!((ready >> j) & 1)) {
#pragma unroll 1
            for (int tries = 0; tries < (1 << 18); tries++) {
              unsigned v; asm volatile("ld.relaxed.gpu.global.u32 %0, [%1];" : "=r"(v) : "l"(fp) : "memory");
              ready |= __ballot_sync(0xffffffffu, v != 0);
              if ((ready >> j) & 1) break;
            }
            asm volatile("fence.acquire.gpu;" ::: "memory");
            fence_async_global();
            STAMP_IF(lane == 0 && j == (own == 0), 42);
          }
          if (!(ROT && j == 0)) mbar_wait(sb + BAR_BE + bo, par);
          STAMP2_IF(lane == 0, 230 + j);
          if (j != own && elect_one()) { mbar_expect_tx(sb + BAR_BF1 + bo, 10240); bulk_g2s(sb + bo * (BUF_BYTES / 8), src + ((j + ROT * c) & 7) * 10240, 10240, sb + BAR_BF1 + bo); }
          bo = (bo + 8) & 24; par ^= (bo == 0);
        }
      } else {
        mbar_wait(sb + BAR_X + 8 * 2, 0); mbar_wait(sb + BAR_X + 8 * 4, 0); mbar_wait(sb + BAR_X + 8 * 5, 0);
        if (elect_one()) {
          if (PF2_ST < 0) {
            asm volatile("cp.async.bulk.prefetch.L2.global [%0], %1;" ::"l"((const char*)w2 + (size_t)bid * 17280), "r"(17280) : "memory");
            asm volatile("cp.async.bulk.prefetch.L2.global [%0], %1;" ::"l"((const char*)wo + (size_t)bid * 6400), "r"(6400) : "memory");
          }
          prefetch_map(&maps.w1_32); prefetch_map(&maps.w1_24);
          prefetch_map(&maps.w2_64); prefetch_map(&maps.w2_32); prefetch_map(&maps.wo_64); prefetch_map(&maps.wo_16); prefetch_map(&maps.y); prefetch_map(&maps.xr);
        }
        __syncwarp();
#pragma unroll 1
        for (int st = 0; st < 4; st++) {
          if (!(CS_IN || CS_HELP) || st) fetch_cs(sb, c, lane, tag, st == 0 ? 0 : st == 1 ? 64 : st == 2 ? 104 : 148, st == 0 ? 64 : st == 1 ? 104 : st == 2 ? 148 : 188);
          if (st == 0) { bar_sync(3, CS_HELP ? 96 : 64); mbar_wait(sb + BAR_X + 8 * 7, 0); mbar_wait(sb + BAR_X + 8 * 9, 0); }
          __syncwarp();
          if (lane == 0) mbar_arrive(sb + (st == 0 ? BAR_PRO : BAR_CS + 8 * st));
          STAMP_IF(lane == 0, 50 + st);
          if (st == PF2_ST) {
            for (int i = lane; i < 135; i += 32) prefetch_l2((const char*)w2 + (size_t)bid * 17280 + i * 128);
            for (int i = lane; i < 50; i += 32) prefetch_l2((const char*)wo + (size_t)bid * 6400 + i * 128);
          }
        }
#pragma unroll 1
        for (int q = 0; q < 22; q++) {
          const int b = q & 3;
          mbar_wait(sb + (q < 4 ? BAR_X + 8 * ((XG_B >> (4 * q)) & 15) : BAR_BE + 8 * b), q < 4 ? 1 : ((q >> 2) - 1) & 1);
          const uint32_t bar = sb + (q < 14 ? BAR_BF : BAR_BF1) + 8 * b;
          if (elect_one()) {
            if (q < 14) {
              const int k0 = q < 8 ? 512 * kap + 64 * q : 512 + 352 * kap + 64 * q;
              const uint32_t dst = sb + b * BUF_BYTES + 16384;
              mbar_expect_tx(bar, q < 13 ? 20480 : 10240);
              if (q < 13 || rank == 0)
              {
                tma_pair(dst, &maps.w2_64, 160 * jn, k0, 32, bar, rank);
                tma_pair(dst + 8192, &maps.w2_64, 160 * jn + 64, k0, 32, bar, rank);
                tma_pair(dst + 16384, &maps.w2_32, 160 * jn + 128, k0, 32, bar, rank);
              }
            } else {
              const int k0 = ((q - 14 + ROT * c) & 7) * 80;
              const int n0 = 160 * jn;
              const uint32_t dst = sb + b * BUF_BYTES + 10240;
              mbar_expect_tx(bar, 25600);
              if (q == 14 + (ROT ? 0 : c)) mbar_arrive(bar);
              tma_pair(dst, &maps.wo_64, n0, k0, 40, bar, rank);
              tma_pair(dst + 10240, &maps.wo_64, n0 + 64, k0, 40, bar, rank);
              tma_pair(dst + 20480, &maps.wo_16, n0 + 128, k0, 40, bar, rank);
            }
          }
          __syncwarp();
        }
      }
    } else {
      if (lane < 25) {
        const int e = r * 50 + 2 * lane;
        const int k = e / 10, j = e - k * 10, h = k / 20;
        const uint2 wv = *(const uint2*)(wphi + c * 1600 + e * 2);
        uint4* dst = g_wphi + c * 800 + j * 8 + (k >> 3) * 80 + (k & 7);
        dst[0] = make_uint4(h == 0 ? wv.x : 0u, h == 1 ? wv.x : 0u, h == 2 ? wv.x : 0u, h == 3 ? wv.x : 0u);
        dst[8] = make_uint4(h == 0 ? wv.y : 0u, h == 1 ? wv.y : 0u, h == 2 ? wv.y : 0u, h == 3 ? wv.y : 0u);
      }
#pragma unroll 1
      for (int i = lane; i < (KV_LL ? 80 : 60); i += 32) ((float4*)g_kv)[bid * (KV_LL ? 80 : 60) + i] = make_float4(0.f, 0.f, 0.f, 0.f);
#pragma unroll 1
      for (int i = 0; i < NPOISON; i++) g_part[(size_t)bid * 1280 + i * 32 + lane] = make_uint4(~0u, ~0u, ~0u, ~0u);
      if (lane == 0) g_oc[bid * 32] = 0;
      if (lane == 1 && bid < 32) g_ha[bid * 32] = 0;
      if (lane == 2 && bid < 32) g_hb[bid * 32] = 0;
      if (lane == 4 && bid < 8) g_kvc[bid * 32] = 0;
      CLUSTER_WAIT();
      bar_sync(6, 96);
      unsigned old = 0;
      if (lane == 0) {
        asm volatile("atom.release.gpu.global.add.u32 %0, [%1], 1;" : "=r"(old) : "l"(g_pro) : "memory");
        STAMP(43);
      }
      if (CS_HELP) { fetch_cs(sb, c, lane, (__shfl_sync(0xffffffffu, old, 0) >> 8) + 1, 0, 64); bar_arrive(3, 96); }
      if (lane == 0) {
        poll_ge(g_pro, (old & ~255u) + 256u);
        STAMP(44);
        mbar_arrive(sb + BAR_GOK);
      }
      __syncwarp();
#pragma unroll 1
      for (int e = 0; e < 4; e++) {
        bar_sync(7 + e, 160);
        if (e == 2) {
          fence_async_smem();
          if (lane < 2) mbar_arrive_cluster(sb + BAR_X + 8 * 9, lane);
        }
        if (lane == 0) {
          if (!(KV_LL && e == 2)) red_release(e == 0 ? &g_ha[(r * 2 + kap) * 32] : e == 1 ? &g_hb[(r * 2 + kap) * 32] : e == 2 ? &g_kvc[c * 32] : &g_oc[(r * 8 + c) * 32]);
          STAMP(45 + e);
        }
        if (lane == 0) {
          if (e == 3) {
            mbar_expect_tx(sb + BAR_XR, 20480);
            tma2d(sb + Y_OFF, &maps.xr, 160 * jn, r * 128 + 64 * kap, sb + BAR_XR);
            tma2d(sb + Y_OFF + 10240, &maps.xr, 160 * jn + 80, r * 128 + 64 * kap, sb + BAR_XR);
          }
        }
        __syncwarp();
      }
    }
    CLUSTER_ARRIVE(); CLUSTER_WAIT();
  } else if (warp < 4) {
    asm volatile("setmaxnreg.inc.sync.aligned.u32 208;");
    const int tid = threadIdx.x, w = warp;
    uint32_t ph = 0;
    const Rel rel(sb, tid);
    const uint32_t zero = gridDim.y - 1;
    uint32_t ha[64];
    uint4* const pown = g_part + (size_t)bid * 1280 + tid;
    CLUSTER_WAIT();
    char* hp = (char*)g_h + (size_t)r * 216 * 2048 + w * 256 + lane * 4;
    {
      float a0[64], a1[64];
      uint32_t prev = BAR_DUMMY;
#pragma unroll 1
      for (int j = 0; j < 13; j++) {
        const uint32_t id = (uint32_t)(P1_SLOT_A >> (4 * j)) & 7;
        const uint64_t db = mkdesc(sb + RING0, 6144, 1024, 1) + id * (SLOT / 16);
        const uint64_t dx = mkdesc(sb, 16, 1024, 1);
        const int k16 = 3 * j;
        const uint64_t da0 = dx + (k16 >> 2) * 1024 + (k16 & 3) * 2, da1 = dx + ((k16 + 1) >> 2) * 1024 + ((k16 + 1) & 3) * 2, da2 = dx + ((k16 + 2) >> 2) * 1024 + ((k16 + 2) & 3) * 2;
        mbar_wait(sb + BAR_X + 8 * ((k16 + 2) >> 2), 0);
        mbar_wait(sb + BAR_RF + 8 * id, (ph >> id) & 1);
        STAMP2_IF(tid == 0, 128 + j);
        wg_fence();
        wgmma_ss(a0, da0, db, j); wgmma_ss(a1, da0 + 512, db, j);
        wg_commit();
        wg_wait<1>();
        rel(prev);
        wgmma_ss(a0, da1, db + 128, 1); wgmma_ss(a1, da1 + 512, db + 128, 1);
        wgmma_ss(a0, da2, db + 256, 1); wgmma_ss(a1, da2 + 512, db + 256, 1);
        wg_commit();
        ph ^= 1u << id; prev = BAR_RE + 8 * id;
      }
      {
        constexpr uint32_t id = (uint32_t)(P1_SLOT_A >> 52) & 7;
        mbar_wait(sb + BAR_RF + 8 * id, (ph >> id) & 1);
        const uint64_t db = mkdesc(sb + RING0 + id * SLOT + 4096, 6144, 1024, 1), da = mkdesc(sb + 9 * 16384 + 96, 16, 1024, 1);
        wg_fence();
        wgmma_ss(a0, da, db, 1); wgmma_ss(a1, da + 512, db, 1);
        wg_commit();
        wg_wait<0>();
        rel(prev); rel(BAR_RE + 8 * id);
      }
      ph = PH_A;
      reg_fence(a0); reg_fence(a1);
      STAMP_IF(tid == 0, 2);
      mbar_wait(sb + BAR_PRO, 0);
      epi_h(a0, a1, ha, sb, CS_W1A, w, lane, zero);
      STAMP_IF(tid == 0, 3);
    }
    {
      float a0[44], a1[44];
      char* const hpa = hp + (size_t)(16 * c) * 2048;
      store_h<64, 0, HA_SPLIT, PACE_A>(ha, hpa);
      STAMP_IF(tid == 0, 12);
      bar_sync(13, 256);
      const uint64_t dx = mkdesc(sb, 16, 1024, 1), dr = mkdesc(sb + RING_OFF, 2048, 512, 2);
#pragma unroll
      for (int k = 0; k < 10; k++) {
        const int pos = k ? (k - 1) % 5 : 3, ppos = (k + 3) % 5;
        const int par = ((PH_A >> pos) & 1) ^ (k > 5) ^ (pos == 3 && k > 0);
        const uint64_t da = dx + k * 1024, db = dr + pos * (SLOT / 16);
        mbar_wait(sb + BAR_RF + 24 + 8 * pos, par);
        STAMP2_IF(tid == 0, 128 + 34 + k);
        wg_fence();
        wgmma_ss(a0, da, db, k); wgmma_ss(a1, da + 512, db, k);
        wg_commit();
        if (k > 1) { wg_wait<1>(); rel(BAR_RE + 24 + 8 * ppos); rel(BAR_X + 8 * (k - 1)); }
        wgmma_ss(a0, da + 2, db + 64, 1); wgmma_ss(a1, da + 514, db + 64, 1);
        constexpr int PER = (64 - HA_SPLIT + HA_STEPS - 1) / HA_STEPS;
#pragma unroll
        for (int i = HA_SPLIT + k * PER; i < HA_SPLIT + (k + 1) * PER; i++)
          if (i < 64) stg32(hpa + (i >> 2) * 2048 + (i & 1) * 128 + ((i >> 1) & 1) * 1024, ha[i < 64 ? i : 0]);
        if (k == HA_STEPS - 1) { bar_arrive(7, 160); STAMP_IF(tid == 0, 4); }
        wgmma_ss(a0, da + 4, db + 384, 1); wgmma_ss(a1, da + 516, db + 384, 1);
        wgmma_ss(a0, da + 6, db + 448, 1); wgmma_ss(a1, da + 518, db + 448, 1);
        wg_commit();
        if (k == 0) {
          wg_wait<0>();
          rel(BAR_RE + 24 + 8 * 3); rel(BAR_X);
          bar_arrive(11, 256);
          bar_sync(12, 256);
        }
      }
      wg_wait<0>();
      rel(BAR_RE + 24 + 8 * 3); rel(BAR_X + 8 * 9);
      reg_fence(a0); reg_fence(a1);
      STAMP_IF(tid == 0, 5);
      uint32_t hb[44];
      mbar_wait(sb + BAR_CS + 16, 0);
      epi_h(a0, a1, hb, sb, CS_W1B, w, lane, zero);
      STAMP_IF(tid == 0, 6);
      store_h<44, 0, 44, PACE_B>(hb, hp + (size_t)(128 + 11 * c) * 2048);
      bar_arrive(8, 160);
      STAMP_IF(tid == 0, 7);
    }
    {
      float a0[80], a1[80];
      bar_sync(13, 256);
#pragma unroll 1
      for (int q = 0; q < 13; q++) {
        const int b = q & 3;
        mbar_wait(sb + BAR_BF + 8 * b, (q >> 2) & 1);
        STAMP2_IF(tid == 0, 192 + q);
        uint64_t da = mkdesc(sb + b * BUF_BYTES, 2048, 128, 0);
        uint64_t db = mkdesc(sb + b * BUF_BYTES + 16384, W2_LBO, W2_SBO, W2_MODE);
        wg_fence();
        wgmma_ss(a0, da, db, q); wgmma_ss(a1, da + 64, db, q);
        wg_commit();
        wg_wait<1>();
        if (!((PAUSE_MASK << 1 | 1) >> q & 1)) rel(BAR_BE + 8 * ((q - 1) & 3));
#pragma unroll
        for (int kk = 1; kk < 4; kk++) { wgmma_ss(a0, da + kk * 256, db + (kk >> 1) * W2_HALF + (kk & 1) * W2_STEP, 1); wgmma_ss(a1, da + kk * 256 + 64, db + (kk >> 1) * W2_HALF + (kk & 1) * W2_STEP, 1); }
        wg_commit();
        if (PAUSE_MASK >> q & 1) {
          wg_wait<0>();
          rel(BAR_BE + 8 * b);
          STAMP_IF(tid == 0 && q == QPAUSE, 14);
          bar_sync(11, 256); bar_sync(12, 256);
        }
      }
      {
        mbar_wait(sb + BAR_BF + 8 * 1, 1);
        uint64_t da = mkdesc(sb + 1 * BUF_BYTES, 2048, 128, 0);
        uint64_t db = mkdesc(sb + 1 * BUF_BYTES + 16384, W2_LBO, W2_SBO, W2_MODE);
        wg_fence();
#pragma unroll
        for (int kk = 0; kk < 2; kk++) { wgmma_ss(a0, da + kk * 256, db + kk * W2_STEP, 1); wgmma_ss(a1, da + kk * 256 + 64, db + kk * W2_STEP, 1); }
        wg_commit();
        wg_wait<1>();
        rel(BAR_BE + 8 * 0);
      }
      wg_wait<0>();
      rel(BAR_BE + 8 * (13 & 3));
      reg_fence(a0); reg_fence(a1);
      STAMP_IF(tid == 0, 8);
      const uint32_t tsend = (uint32_t)clock();
      const int partner = bid ^ 64;
      uint4* pd = g_part + (size_t)partner * 1280 + tid;
      if (kap) {
#pragma unroll
        for (int i = 0; i < 10; i++) st_relaxed128(pd + i * 128, pack_bf16(a0[8 * i], a0[8 * i + 1]), pack_bf16(a0[8 * i + 2], a0[8 * i + 3]), pack_bf16(a0[8 * i + 4], a0[8 * i + 5]), pack_bf16(a0[8 * i + 6], a0[8 * i + 7]));
        if (SEND_PIN) mbar_wait(sb + BAR_GOK, 0);
#pragma unroll
        for (int i = 0; i < 40; i++) { a0[i] = 0.5f * a1[i]; a1[i] = 0.5f * a1[40 + i]; }
      } else {
#pragma unroll
        for (int i = 0; i < 10; i++) st_relaxed128(pd + i * 128, pack_bf16(a1[8 * i], a1[8 * i + 1]), pack_bf16(a1[8 * i + 2], a1[8 * i + 3]), pack_bf16(a1[8 * i + 4], a1[8 * i + 5]), pack_bf16(a1[8 * i + 6], a1[8 * i + 7]));
        if (SEND_PIN) mbar_wait(sb + BAR_GOK, 0);
#pragma unroll
        for (int i = 0; i < 40; i++) { a1[i] = 0.5f * a0[40 + i]; a0[i] *= 0.5f; }
      }
      STAMP_IF(tid == 0, 9);
      bar_sync(4, 256);
      if (LL_WAIT) while ((uint32_t)clock() - tsend < LL_WAIT) {}
      uint4 pv[10];
#pragma unroll 1
      for (int tries = 0; tries < (1 << 16); tries++) {
        if (ld_relaxed128(pown + 9 * 128).w == ~0u) continue;
        uint32_t mx = 0;
#pragma unroll
        for (int i = 0; i < 10; i++) pv[i] = ld_relaxed128(pown + i * 128);
#pragma unroll
        for (int i = 0; i < 10; i++) mx = max(max(mx, max(pv[i].x, pv[i].y)), max(pv[i].z, pv[i].w));
        if (mx != ~0u) break;
      }
      STAMP_IF(tid == 0, 10);
#pragma unroll
      for (int i = 0; i < 5; i++) {
        const uint32_t pp[4] = {pv[5 + i].x, pv[5 + i].y, pv[5 + i].z, pv[5 + i].w};
        uint32_t o[4];
#pragma unroll
        for (int u = 0; u < 4; u++) o[u] = pack_bf16(silu_half(fmaf(bf_lo(pp[u]), 0.5f, a1[8 * i + 2 * u])), silu_half(fmaf(bf_hi(pp[u]), 0.5f, a1[8 * i + 2 * u + 1])));
        sts128(sb + G_OFF + (i * 128 + tid) * 16, o[0], o[1], o[2], o[3]);
      }
      bar_arrive(5, 256);
      STAMP_IF(tid == 0, 11);
      mbar_wait(sb + BAR_XR, 1);
      const uint32_t ya = sb + Y_OFF + (16 * w + (lane & 15)) * 160 + (lane >> 4) * 16;
#pragma unroll
      for (int i = 0; i < 5; i++) {
        const uint32_t pp[4] = {pv[i].x, pv[i].y, pv[i].z, pv[i].w};
        uint32_t xv[4];
        ldsm4(ya + i * 32, xv[0], xv[1], xv[2], xv[3]);
#pragma unroll
        for (int u = 0; u < 4; u++) {
          a0[8 * i + 2 * u] = silu_half(fmaf(bf_lo(pp[u]), 0.5f, a0[8 * i + 2 * u])); a0[8 * i + 2 * u + 1] = silu_half(fmaf(bf_hi(pp[u]), 0.5f, a0[8 * i + 2 * u + 1]));
          a1[8 * i + 2 * u] = bf_lo(xv[u]); a1[8 * i + 2 * u + 1] = bf_hi(xv[u]);
        }
      }
      mbar_wait(sb + BAR_GOK, 0);
      bar_sync(1, 256);
#pragma unroll
      for (int i = 0; i < 5; i++) {
        const uint4 u = lds128(sb + O_OFF + (2 * i * 128 + tid) * 16), v = lds128(sb + O_OFF + ((2 * i + 1) * 128 + tid) * 16);
        stsm4(ya + i * 32, pack_bf16(fmaf(__uint_as_float(u.x), a0[8 * i], a1[8 * i]), fmaf(__uint_as_float(u.y), a0[8 * i + 1], a1[8 * i + 1])),
              pack_bf16(fmaf(__uint_as_float(u.z), a0[8 * i + 2], a1[8 * i + 2]), fmaf(__uint_as_float(u.w), a0[8 * i + 3], a1[8 * i + 3])),
              pack_bf16(fmaf(__uint_as_float(v.x), a0[8 * i + 4], a1[8 * i + 4]), fmaf(__uint_as_float(v.y), a0[8 * i + 5], a1[8 * i + 5])),
              pack_bf16(fmaf(__uint_as_float(v.z), a0[8 * i + 6], a1[8 * i + 6]), fmaf(__uint_as_float(v.w), a0[8 * i + 7], a1[8 * i + 7])));
      }
      fence_async_smem();
      __syncwarp();
      if (elect_one()) {
        asm volatile("cp.async.bulk.tensor.2d.global.shared::cta.tile.bulk_group [%0, {%2, %3}], [%1];" ::"l"(&maps.y), "r"(sb + Y_OFF + w * 2560), "r"(160 * jn), "r"(r * 128 + 64 * kap + 16 * w) : "memory");
        asm volatile("cp.async.bulk.commit_group;\ncp.async.bulk.wait_group.read 0;" ::: "memory");
      }
      __syncwarp();
      STAMP_IF(tid == 0, 37);
    }
    CLUSTER_ARRIVE(); CLUSTER_WAIT();
  } else {
    asm volatile("setmaxnreg.inc.sync.aligned.u32 240;");
    const int tid = threadIdx.x - 128, w = warp - 4;
    const int g = lane >> 2, t = lane & 3;
    uint32_t ph = 0;
    const Rel rel(sb, tid);
    uint32_t vf0[20], vf1[20];
    {
      CLUSTER_WAIT();
      float a0[40], a1[40];
#pragma unroll 1
      for (int k = 0; k < 10; k++) {
        const uint32_t id = (uint32_t)(P1_SLOT_V >> (4 * k)) & 7;
        const uint64_t da = mkdesc(sb, 16, 1024, 1) + k * 1024, db = mkdesc(sb + RING0, 2048, 512, 2) + id * (SLOT / 16);
        mbar_wait(sb + BAR_X + 8 * k, 0); mbar_wait(sb + BAR_RF1 + 8 * id, (ph >> id) & 1);
        STAMP2_IF(tid == 0, 142 + k);
        wg_fence();
        wgmma_ss(a0, da, db, k); wgmma_ss(a1, da + 512, db, k); wgmma_ss(a0, da + 2, db + 64, 1); wgmma_ss(a1, da + 514, db + 64, 1);
        wgmma_ss(a0, da + 4, db + 384, 1); wgmma_ss(a1, da + 516, db + 384, 1); wgmma_ss(a0, da + 6, db + 448, 1); wgmma_ss(a1, da + 518, db + 448, 1);
        wg_commit();
        ph ^= 1u << id;
        wg_wait<0>();
        rel(BAR_RE + 8 * id);
      }
      ph = PH_V;
      reg_fence(a0); reg_fence(a1);
      STAMP_IF(tid == 0, 18);
      mbar_wait(sb + BAR_PRO, 0);
      RowStats st; load_stats(st, sb, w, g);
#pragma unroll
      for (int j = 0; j < 20; j++) {
        vf0[j] = pack_bf16(a0[2 * j] * st.rstd[0][j & 1], a0[2 * j + 1] * st.rstd[0][j & 1]);
        vf1[j] = pack_bf16(a1[2 * j] * st.rstd[1][j & 1], a1[2 * j + 1] * st.rstd[1][j & 1]);
      }
      STAMP_IF(tid == 0, 19);
    }
    const int nb = (5 * w) >> 1;
    auto* kp = g_kv + (c * 4 + w) * (KV_LL ? 320 : 480) + lane;
    asm volatile("" : "+l"(kp));
    const uint32_t pa = sb + PHI_OFF + t * PHI_HS + (16 * w + g) * 80;
    uint32_t o00[20], o01[20], o10[20], o11[20];
#pragma unroll 1
    for (int it = 0; it < 2; it++) {
      float a0[40], a1[40];
      uint32_t so = POS_K + it, prev_r = BAR_DUMMY, prev_x = BAR_DUMMY;
      tile_loop(a0, a1, sb, BAR_RF1, ph, so, 0, 10, rel, prev_r, prev_x, it * 8, -1, 128 + 24 + 20 * it, clk0);
      bar_arrive(13, 256);
      RowStats st; load_stats(st, sb, w, g);
      mbar_wait(sb + BAR_CS + 8 + 16 * it, 0);
      uint32_t f0[20], f1[20];
      if (it) {
        const uint32_t va = sb + V_OFF + (16 * w + (lane & 15)) * V_PITCH + (lane >> 4) * 16;
        uint32_t e[2][2];
#pragma unroll
        for (int m = 0; m < 2; m++)
#pragma unroll
          for (int i = 0; i < 2; i++) e[m][i] = (t & 1) ? 0u : pack_bf16(1.f, st.mean[m][i] * st.rstd[m][i]);
        uint32_t av = sb + V_OFF + ((lane >> 4) * 8 + (lane & 7)) * V_PITCH + w * 48 + ((lane >> 3) & 1) * 16;
        uint32_t av2 = sb + V_OFF + (lane & 15) * V_PITCH + w * 48 + 32;
        uint32_t bp = sb + PHIK0_OFF + w * PHI_HS + (lane & 15) * 80 + (lane >> 4) * 16;
        wg_wait<0>();
        reg_fence(a0); reg_fence(a1);
        STAMP_IF(tid == 0, 22);
        bar_sync(2, 128);
#pragma unroll
        for (int m = 0; m < 2; m++) {
          const uint32_t (&vf)[20] = m ? vf1 : vf0;
          const uint32_t vb = va + m * 64 * V_PITCH;
#pragma unroll
          for (int p = 0; p < 2; p++) {
            const int j = 10 * p;
            stsm4(vb + p * 96, vf[j], vf[j + 1], vf[j + 2], vf[j + 3]);
            stsm4(vb + p * 96 + 32, t < 2 ? vf[j + 4] : e[m][0], t < 2 ? vf[j + 5] : e[m][1], t < 2 ? e[m][0] : vf[j + 4], t < 2 ? e[m][1] : vf[j + 5]);
            stsm4(vb + p * 96 + 64, vf[j + 6], vf[j + 7], vf[j + 8], vf[j + 9]);
          }
        }
        store_phi(pa + (PHIK0_OFF - PHI_OFF), o00); store_phi(pa + (PHIK0_OFF - PHI_OFF) + 640, o01);
        store_phi(pa + (PHIK1_OFF - PHI_OFF), o10); store_phi(pa + (PHIK1_OFF - PHI_OFF) + 640, o11);
        float kv[2][5][4];
#pragma unroll
        for (int i = 0; i < 10; i++) { kv[i / 5][i % 5][0] = 0.f; kv[i / 5][i % 5][1] = 0.f; kv[i / 5][i % 5][2] = 0.f; kv[i / 5][i % 5][3] = 0.f; }
#pragma unroll 1
        for (int m = 0; m < 2; m++) {
          if (m == 0) { bar_sync(11, 256); STAMP_IF(tid == 0, 23); }
          uint32_t a[4][4], a2[4][2], b[4][10];
#pragma unroll
          for (int ks = 0; ks < 4; ks++) {
            ldsm4t(av + ks * 16 * V_PITCH, a[ks][0], a[ks][1], a[ks][2], a[ks][3]);
            ldsm4t(bp + ks * 1280, b[ks][0], b[ks][1], b[ks][2], b[ks][3]);
            ldsm2t(av2 + ks * 16 * V_PITCH, a2[ks][0], a2[ks][1]);
            ldsm4t(bp + ks * 1280 + 32, b[ks][4], b[ks][5], b[ks][6], b[ks][7]);
            ldsm2t(bp + ks * 1280 + 64, b[ks][8], b[ks][9]);
          }
#pragma unroll
          for (int ks = 0; ks < 4; ks++)
#pragma unroll
            for (int nf = 0; nf < 5; nf++) {
              mma16816(kv[0][nf], a[ks][0], a[ks][1], a[ks][2], a[ks][3], b[ks][2 * nf], b[ks][2 * nf + 1]);
              mma16816(kv[1][nf], a2[ks][0], 0u, a2[ks][1], 0u, b[ks][2 * nf], b[ks][2 * nf + 1]);
            }
          av += 64 * V_PITCH; av2 += 64 * V_PITCH; bp += PHIK1_OFF - PHIK0_OFF;
        }
#pragma unroll
        for (int nf = 0; nf < 5; nf++) {
          asm volatile("red.global.add.v2.f32 [%0], {%1, %2};" ::"l"(kp + nf * 32), "f"(kv[0][nf][0]), "f"(kv[0][nf][1]) : "memory");
          asm volatile("red.global.add.v2.f32 [%0], {%1, %2};" ::"l"(kp + (5 + nf) * 32), "f"(kv[0][nf][2]), "f"(kv[0][nf][3]) : "memory");
          asm volatile("red.global.add.v2.f32 [%0], {%1, %2};" ::"l"(kp + (10 + nf) * 32), "f"(kv[1][nf][0]), "f"(kv[1][nf][1]) : "memory");
        }
        bar_arrive(9, 160);
        if (B2_SPLIT) bar_arrive(12, 256);
        STAMP_IF(tid == 0, 24);
      } else {
        wg_wait<0>();
        reg_fence(a0); reg_fence(a1);
        STAMP_IF(tid == 0, 20);
        rel(prev_r);
      }
      fix_pack(a0, a1, f0, f1, st, sb + CS_OFF + ((it ? CS_Q : CS_K) + 2 * t) * 4);
      mbar_wait(sb + BAR_WPHI, it);
      if (!it || B2_SPLIT) bar_sync(11, 256);
      STAMP_IF(tid == 0, it ? 36 : 32);
      wg_fence();
      phi_gemm(a0, f0, sb);
      phi_gemm(a1, f1, sb);
      bar_arrive(12, 256);
      wg_wait<0>();
      if (!it) rel(BAR_RE + 24 + 8 * 4);
      reg_fence(a0); reg_fence(a1);
      dual_softmax(a0, 0, st.rstd[0][0] * kLog2e, o00);
      dual_softmax(a0, 1, st.rstd[0][1] * kLog2e, o01);
      dual_softmax(a1, 0, st.rstd[1][0] * kLog2e, o10);
      dual_softmax(a1, 1, st.rstd[1][1] * kLog2e, o11);
      STAMP_IF(tid == 0, it ? 25 : 33);
    }
    bar_sync(2, 128);
    store_phi(pa, o00); store_phi(pa + 640, o01); store_phi(pa + PHI_HALF, o10); store_phi(pa + PHI_HALF + 640, o11);
    mbar_wait(sb + BAR_KV, 0);
    STAMP_IF(tid == 0, 26);
    {
      uint32_t kb[15];
      float csv[3];
#pragma unroll
      for (int dn = 0; dn < 3; dn++) csv[dn] = lds32f(sb + CS_OFF + (CS_V + nb * 8 + dn * 8 + g) * 4);
      if ((w & 1) && g < 4) csv[0] = 0.f;
      if (!(w & 1) && g >= 4) csv[2] = 0.f;
#pragma unroll
      for (int nf = 0; nf < 5; nf++) {
        const float2 mu = lds64f(sb + V_OFF + (w * 480 + ((w & 1) ? 4 : 340) + nf * 32 + t) * 8);
#pragma unroll
        for (int dn = 0; dn < 3; dn++) {
          const float2 v = lds64f(sb + V_OFF + (w * 480 + (dn * 5 + nf) * 32 + lane) * 8);
          kb[dn * 5 + nf] = pack_bf16(fmaf(-csv[dn], mu.x, v.x), fmaf(-csv[dn], mu.y, v.y));
        }
      }
      const uint32_t ap = sb + PHI_OFF + w * PHI_HS + (lane & 15) * 80 + (lane >> 4) * 16;
      float o[8][3][4];
      asm volatile("" ::"r"(kb[0]), "r"(kb[14]) : "memory");
      bar_sync(11, 256);
      STAMP_IF(tid == 0, 34);
#pragma unroll
      for (int mt = 0; mt < 8; mt++) {
        uint32_t a[10];
        const uint32_t aa = ap + (mt >> 2) * PHI_HALF + (mt & 3) * 1280;
        ldsm4(aa, a[0], a[1], a[2], a[3]);
        ldsm4(aa + 32, a[4], a[5], a[6], a[7]);
        ldsm2(aa + 64, a[8], a[9]);
#pragma unroll
        for (int dn = 0; dn < 3; dn++) {
          o[mt][dn][0] = 0.f; o[mt][dn][1] = 0.f; o[mt][dn][2] = 0.f; o[mt][dn][3] = 0.f;
          mma16816(o[mt][dn], a[0], a[1], a[2], a[3], kb[dn * 5], kb[dn * 5 + 1]);
          mma16816(o[mt][dn], a[4], a[5], a[6], a[7], kb[dn * 5 + 2], kb[dn * 5 + 3]);
          mma1688(o[mt][dn], a[8], a[9], kb[dn * 5 + 4]);
        }
      }
      {
        uint32_t dep = gridDim.y - 1;
#pragma unroll
        for (int mt = 0; mt < 8; mt++) dep &= __float_as_uint(o[mt][0][0]) & __float_as_uint(o[mt][1][0]) & __float_as_uint(o[mt][2][0]);
        if (!B3_LONG) bar_arrive(12 + dep, 256);
        if (B3_PIN) mbar_wait(sb + BAR_GOK, 0);
      }
      const uint32_t op = sb + O_OFF + nb * 1024 + lane * 4;
      const uint32_t st0 = !(w & 1) || t >= 2, st2 = (w & 1) || t < 2;
      const int dsrc = (lane & ~3) | ((w & 1) ? 0 : 2);
      float rr[16];
#pragma unroll
      for (int mt = 0; mt < 8; mt++) {
        rr[2 * mt] = rcp(__shfl_sync(0xffffffffu, (w & 1) ? o[mt][0][0] : o[mt][2][0], dsrc) + 1e-6f);
        rr[2 * mt + 1] = rcp(__shfl_sync(0xffffffffu, (w & 1) ? o[mt][0][2] : o[mt][2][2], dsrc) + 1e-6f);
      }
#pragma unroll
      for (int mt = 0; mt < 8; mt++) {
        const float r0 = rr[2 * mt], r1 = rr[2 * mt + 1];
        const uint32_t q = op + (mt >> 2) * 10240 + (mt & 3) * 256;
        sts32p(q, pack_bf16(o[mt][0][0] * r0, o[mt][0][1] * r0), st0); sts32p(q + 128, pack_bf16(o[mt][0][2] * r1, o[mt][0][3] * r1), st0);
        sts32(q + 1024, pack_bf16(o[mt][1][0] * r0, o[mt][1][1] * r0)); sts32(q + 1024 + 128, pack_bf16(o[mt][1][2] * r1, o[mt][1][3] * r1));
        sts32p(q + 2048, pack_bf16(o[mt][2][0] * r0, o[mt][2][1] * r0), st2); sts32p(q + 2048 + 128, pack_bf16(o[mt][2][2] * r1, o[mt][2][3] * r1), st2);
      }
      fence_async_smem();
      bar_arrive(4, 256);
      bar_sync(2, 128);
      uint4* og = g_o + ((size_t)r * 16 + c) * 640 + tid;
#pragma unroll
      for (int i = 0; i < 10; i++) og[(i / 5) * 5120 + (i % 5) * 128] = lds128(sb + O_OFF + (i * 128 + tid) * 16);
      bar_arrive(10, 160);
      if (B3_LONG) bar_arrive(12, 256);
      STAMP_IF(tid == 0, 27);
    }
    {
      float sa[80];
#pragma unroll 1
      for (int q = 14; q < 22; q++) {
        const int b = q & 3;
        const uint64_t da = mkdesc(sb + (q == 14 + (ROT ? 0 : c) ? O_OFF + kap * 10240 : b * BUF_BYTES), 1024, 128, 0);
        const uint64_t db = mkdesc(sb + b * BUF_BYTES + 10240, 10240, 1024, 1);
        mbar_wait(sb + BAR_BF1 + 8 * b, ((q - 14) >> 2) & 1);
        STAMP2_IF(tid == 0, 192 + q);
        wg_fence();
        wgmma_ss(sa, da, db, q - 14);
        wg_commit();
        wg_wait<1>();
        if (q > 14 && q <= 18) rel(BAR_BE + 8 * ((q - 1) & 3));
#pragma unroll
        for (int kk = 1; kk < 5; kk++) wgmma_ss(sa, da + kk * 128, db + kk * 128, 1);
        wg_commit();
      }
      CLUSTER_ARRIVE();
      const uint32_t ya = sb + Y_OFF + (64 + 16 * w + (lane & 15)) * 160 + (lane >> 4) * 16;
      float xf[40];
      mbar_wait(sb + BAR_XR, 1);
#pragma unroll
      for (int i = 0; i < 5; i++) {
        uint32_t xv[4];
        ldsm4(ya + i * 32, xv[0], xv[1], xv[2], xv[3]);
#pragma unroll
        for (int u = 0; u < 4; u++) { xf[8 * i + 2 * u] = bf_lo(xv[u]); xf[8 * i + 2 * u + 1] = bf_hi(xv[u]); }
      }
      mbar_wait(sb + BAR_GOK, 0);
      wg_wait<0>();
      reg_fence(sa);
      STAMP_IF(tid == 0, 29);
      if (!ROT && c == 7) bar_sync(2, 128);
#pragma unroll
      for (int i = 0; i < 10; i++) sts128(sb + O_OFF + (i * 128 + tid) * 16, __float_as_uint(sa[4 * i]), __float_as_uint(sa[4 * i + 1]), __float_as_uint(sa[4 * i + 2]), __float_as_uint(sa[4 * i + 3]));
      bar_arrive(1, 256);
      bar_sync(5, 256);
      STAMP_IF(tid == 0, 30);
#pragma unroll
      for (int i = 0; i < 5; i++) {
        const uint4 gv = lds128(sb + G_OFF + (i * 128 + tid) * 16);
        const uint32_t gg[4] = {gv.x, gv.y, gv.z, gv.w};
        uint32_t y[4];
#pragma unroll
        for (int u = 0; u < 4; u++) y[u] = pack_bf16(fmaf(sa[40 + 8 * i + 2 * u], bf_lo(gg[u]), xf[8 * i + 2 * u]), fmaf(sa[40 + 8 * i + 2 * u + 1], bf_hi(gg[u]), xf[8 * i + 2 * u + 1]));
        stsm4(ya + i * 32, y[0], y[1], y[2], y[3]);
      }
      fence_async_smem();
      __syncwarp();
      if (elect_one()) {
        asm volatile("cp.async.bulk.tensor.2d.global.shared::cta.tile.bulk_group [%0, {%2, %3}], [%1];" ::"l"(&maps.y), "r"(sb + Y_OFF + 10240 + w * 2560), "r"(160 * jn + 80), "r"(r * 128 + 64 * kap + 16 * w) : "memory");
        asm volatile("cp.async.bulk.commit_group;" ::: "memory");
      }
      asm volatile("cp.async.bulk.wait_group.read 0;" ::: "memory");
      __syncwarp();
      STAMP_IF(tid == 0, 31);
    }
    CLUSTER_WAIT();
  }
}

typedef CUresult (*EncodeFn)(CUtensorMap*, CUtensorMapDataType, cuuint32_t, void*, const cuuint64_t*, const cuuint64_t*, const cuuint32_t*,
                             const cuuint32_t*, CUtensorMapInterleave, CUtensorMapSwizzle, CUtensorMapL2promotion, CUtensorMapFloatOOBfill);

void make_map(EncodeFn fn, CUtensorMap* m, const void* ptr, uint64_t cols, uint64_t rows, uint32_t bc, uint32_t br, CUtensorMapSwizzle sw, uint32_t panels = 0) {
  cuuint64_t dims[3] = {cols, rows, panels};
  cuuint64_t strides[2] = {cols * 2, (cuuint64_t)bc * 2};
  cuuint32_t box[3] = {bc, br, panels}, es[3] = {1, 1, 1};
  CUresult res = fn(m, CU_TENSOR_MAP_DATA_TYPE_BFLOAT16, panels ? 3 : 2, const_cast<void*>(ptr), dims, strides, box, es, CU_TENSOR_MAP_INTERLEAVE_NONE,
     sw, CU_TENSOR_MAP_L2_PROMOTION_L2_128B, CU_TENSOR_MAP_FLOAT_OOB_FILL_NONE);
  (void)res;
}

}

extern "C" void kernel_launch(void* const* d_in, const int* in_sizes, int n_in, void* d_out, int out_size) {
  (void)in_sizes; (void)n_in; (void)out_size;
  const __nv_bfloat16* x = (const __nv_bfloat16*)d_in[0];
  const __nv_bfloat16* wqkv = (const __nv_bfloat16*)d_in[1];
  const __nv_bfloat16* wphi = (const __nv_bfloat16*)d_in[2];
  const __nv_bfloat16* wo = (const __nv_bfloat16*)d_in[3];
  const __nv_bfloat16* w1 = (const __nv_bfloat16*)d_in[5];
  const __nv_bfloat16* w2 = (const __nv_bfloat16*)d_in[6];
  void* fnp = nullptr;
  cudaDriverEntryPointQueryResult qr;
  cudaGetDriverEntryPoint("cuTensorMapEncodeTiled", &fnp, cudaEnableDefault, &qr);
  EncodeFn fn = (EncodeFn)fnp;
  Maps maps;
  const CUtensorMapSwizzle S128 = CU_TENSOR_MAP_SWIZZLE_128B, S64 = CU_TENSOR_MAP_SWIZZLE_64B;
  make_map(fn, &maps.x, x, 640, 2048, 64, 128, S128);
  make_map(fn, &maps.w1a, w1, 1728, 640, 64, 48, S128);
  make_map(fn, &maps.q32, wqkv, 1920, 640, 32, 32, S64, 2);
  make_map(fn, &maps.q16, wqkv, 1920, 640, 16, 32, S64);
  make_map(fn, &maps.jq, wqkv, 1920, 640, 64, 128, S128);
  make_map(fn, &maps.jw, w1, 1728, 640, 64, 128, S128);
  make_map(fn, &maps.w1_32, w1, 1728, 640, 32, 32, S64, 2);
  make_map(fn, &maps.w1_24, w1, 1728, 640, 24, 32, S64);
  make_map(fn, &maps.w2_64, w2, 640, 1728, 64, 32, S128);
  make_map(fn, &maps.w2_32, w2, 640, 1728, 32, 32, S128);
  make_map(fn, &maps.wo_64, wo, 640, 640, 64, 40, S128);
  make_map(fn, &maps.wo_16, wo, 640, 640, 32, 40, S128);
  make_map(fn, &maps.xr, x, 640, 2048, 80, 64, CU_TENSOR_MAP_SWIZZLE_NONE);
  make_map(fn, &maps.y, d_out, 640, 2048, 80, 16, CU_TENSOR_MAP_SWIZZLE_NONE);
  cudaFuncSetAttribute(fused_kernel, cudaFuncAttributeMaxDynamicSharedMemorySize, SMEM_BYTES);
  fused_kernel<<<132, 384, SMEM_BYTES, cudaStreamPerThread>>>(x, wqkv, wphi, w1, w2, wo, maps);
}
```
